```python
import torch

def _softmax(x, axis=-1):
    return torch.softmax(x, dim=axis)
def _gelu(x):
    return torch.nn.functional.gelu(x, approximate="tanh")
def _silu(x):
    return torch.nn.functional.silu(x)
def _sigmoid(x):
    return torch.sigmoid(x)
def _layernorm(x, axis=-1, eps=1e-5):
    m = x.mean(dim=axis, keepdim=True)
    v = x.var(dim=axis, keepdim=True, unbiased=False)
    return (x - m) / torch.sqrt(v + eps)
def _scatter_add(tgt, idx, src, axis=0):
    return tgt.clone().index_add_(axis, idx, src)
def _segment_sum(src, seg, n):
    out = torch.zeros((n,) + src.shape[1:], dtype=src.dtype)
    return out.index_add_(0, seg, src)
def _pad(x, pw):
    flat = tuple(v for pair in reversed(pw) for v in pair)
    return torch.nn.functional.pad(x, flat)

kernel_name = 'standalone__paged_block_table_kv_radixattention__decode'

def setup_inputs():

    _w = (lambda a: (lambda t: t.to(torch.bfloat16) if t.is_floating_point() else t)(torch.as_tensor(a)))
    B, H, Hkv, Dh = 1, 32, 16, 128
    Lk = 65536
    bs = 16
    nb = max(2, Lk // bs)
    P = max(1, nb // 2)
    n_phys = P + B * (nb - P)
    shared = torch.arange(P, dtype=torch.int64)
    priv = P + torch.arange(B * (nb - P), dtype=torch.int64).reshape(B, nb - P)
    bt = torch.cat([torch.tile(shared[None, :], (B, 1)), priv], dim=1)
    ctx = nb * bs - (torch.arange(1, B + 1, dtype=torch.int64) * 2654435761) % max(1, (nb * bs - P * bs) // 2)
    return {
        "q": _w((lambda *s: torch.randn(*s, dtype=torch.bfloat16) * 0.8)(B, H, Dh)),
        "k_cache": _w((lambda *s: torch.randn(*s, dtype=torch.bfloat16) * 0.8)(n_phys, bs, Hkv, Dh)),
        "v_cache": _w((lambda *s: torch.randn(*s, dtype=torch.bfloat16) * 0.05)(n_phys, bs, Hkv, Dh)),
        "block_table": _w(bt.to(torch.int64)),
        "ctx_lens": _w(torch.as_tensor(ctx).to(torch.int64)),
    }

def reference(q, k_cache, v_cache, block_table, ctx_lens):
    B, H, Dh = q.shape
    n_phys, bs, Hkv, _ = k_cache.shape
    nb = block_table.shape[1]
    Lk = nb * bs
    rep = H // Hkv
    k = k_cache[block_table].reshape(B, Lk, Hkv, Dh)
    v = v_cache[block_table].reshape(B, Lk, Hkv, Dh)
    k = (lambda x, n, axis: torch.repeat_interleave(x, n, dim=axis))(k, rep, axis=2)
    v = (lambda x, n, axis: torch.repeat_interleave(x, n, dim=axis))(v, rep, axis=2)
    scores = torch.einsum("bhd,bkhd->bhk", q, k) * (Dh ** -0.5)
    pos = torch.arange(Lk)
    valid = pos[None, :] < ctx_lens[:, None]
    scores = torch.where(valid[:, None, :], scores, -1e9)
    p = _softmax(scores, axis=-1)
    return torch.einsum("bhk,bkhd->bhd", p, v)
```

```cpp
#include <cuda_runtime.h>
#include <cuda_bf16.h>
#include <stdint.h>

namespace {

constexpr int H = 32, HKV = 16, DH = 128, BS = 16;
constexpr int TOK_BYTES = HKV * DH * 2;
constexpr int CH_TOK = 4;
constexpr int CH_BYTES = CH_TOK * TOK_BYTES;
constexpr int STAGE_BYTES = 2 * CH_BYTES;
constexpr int NSTAGE = 6;
constexpr int NCONS = 4;
constexpr int NWARPS = NCONS + NSTAGE;
constexpr int NTHREADS = NWARPS * 32;
constexpr int MAXG = 160;
constexpr int SMEM_BYTES = NSTAGE * STAGE_BYTES;

constexpr float NEG_INIT = -1.0e30f;
constexpr float LOG2E = 1.4426950408889634f;
constexpr float QK_SCALE = 0.08838834764831845f * LOG2E;
constexpr float MASKED = -998244352.0f * LOG2E;

__device__ float g_part_o[H * MAXG * DH];
__device__ float2 g_part_ml[H * MAXG];
__device__ unsigned int g_work;
__device__ unsigned int g_arrive;
__device__ unsigned int g_exit;

__device__ __forceinline__ uint32_t smem_u32(const void* p) { return (uint32_t)__cvta_generic_to_shared(p); }
__device__ __forceinline__ void mbar_init(uint32_t bar, int cnt) {
    asm volatile("mbarrier.init.shared::cta.b64 [%0], %1;" ::"r"(bar), "r"(cnt) : "memory");
}
__device__ __forceinline__ void mbar_expect_tx(uint32_t bar, uint32_t bytes) {
    asm volatile("mbarrier.arrive.expect_tx.shared::cta.b64 _, [%0], %1;" ::"r"(bar), "r"(bytes) : "memory");
}
__device__ __forceinline__ void mbar_arrive(uint32_t bar) {
    asm volatile("mbarrier.arrive.shared::cta.b64 _, [%0];" ::"r"(bar) : "memory");
}
__device__ __forceinline__ bool mbar_try(uint32_t bar, uint32_t parity) {
    uint32_t ok;
    asm volatile(
        "{\n.reg .pred p;\n"
        "mbarrier.try_wait.parity.shared::cta.b64 p, [%1], %2;\n"
        "selp.u32 %0, 1, 0, p;\n}"
        : "=r"(ok) : "r"(bar), "r"(parity) : "memory");
    return ok != 0;
}
__device__ __forceinline__ void mbar_wait(uint32_t bar, uint32_t parity) {
    if (mbar_try(bar, parity)) return;
    uint32_t n = 0;
    while (!mbar_try(bar, parity)) {
        if (++n > (1u << 24)) __trap();
    }
}
__device__ __forceinline__ void bulk_g2s(uint32_t dst, const void* src, uint32_t bytes, uint32_t bar) {
    asm volatile("cp.async.bulk.shared::cluster.global.mbarrier::complete_tx::bytes [%0], [%1], %2, [%3];"
                 ::"r"(dst), "l"(src), "r"(bytes), "r"(bar) : "memory");
}
__device__ __forceinline__ void ldsm4(uint32_t (&r)[4], uint32_t addr) {
    asm volatile("ldmatrix.sync.aligned.m8n8.x4.shared.b16 {%0,%1,%2,%3}, [%4];"
                 : "=r"(r[0]), "=r"(r[1]), "=r"(r[2]), "=r"(r[3]) : "r"(addr) : "memory");
}
__device__ __forceinline__ void ldsm4t(uint32_t (&r)[4], uint32_t addr) {
    asm volatile("ldmatrix.sync.aligned.m8n8.x4.trans.shared.b16 {%0,%1,%2,%3}, [%4];"
                 : "=r"(r[0]), "=r"(r[1]), "=r"(r[2]), "=r"(r[3]) : "r"(addr) : "memory");
}
__device__ __forceinline__ void mma16816(float (&c)[4], const uint32_t (&a)[4], uint32_t b0, uint32_t b1) {
    asm volatile("mma.sync.aligned.m16n8k16.row.col.f32.bf16.bf16.f32 {%0,%1,%2,%3}, {%4,%5,%6,%7}, {%8,%9}, {%0,%1,%2,%3};"
                 : "+f"(c[0]), "+f"(c[1]), "+f"(c[2]), "+f"(c[3])
                 : "r"(a[0]), "r"(a[1]), "r"(a[2]), "r"(a[3]), "r"(b0), "r"(b1));
}
__device__ __forceinline__ uint32_t movm(uint32_t a) {
    uint32_t d;
    asm volatile("movmatrix.sync.aligned.m8n8.trans.b16 %0, %1;" : "=r"(d) : "r"(a));
    return d;
}
__device__ __forceinline__ uint32_t pack_bf16(float lo, float hi) {
    uint32_t d;
    asm("cvt.rn.bf16x2.f32 %0, %1, %2;" : "=r"(d) : "f"(hi), "f"(lo));
    return d;
}
__device__ __forceinline__ float ex2(float x) {
    float y;
    asm("ex2.approx.ftz.f32 %0, %1;" : "=f"(y) : "f"(x));
    return y;
}
__device__ __forceinline__ int ld_nc_i32(const int* p) {
    int v;
    asm volatile("ld.global.nc.s32 %0, [%1];" : "=r"(v) : "l"(p));
    return v;
}

__global__ void __launch_bounds__(NTHREADS, 1)
decode_kernel(const __nv_bfloat16* __restrict__ q, const uint8_t* __restrict__ kc, const uint8_t* __restrict__ vc,
              const int* __restrict__ bt, const int* __restrict__ ctx_ptr, __nv_bfloat16* __restrict__ out, int nb)
{
    extern __shared__ __align__(1024) uint8_t smem[];
    __shared__ __align__(8) uint64_t s_full[NSTAGE], s_empty[NSTAGE];
    __shared__ int s_chunk[NSTAGE];
    __shared__ __align__(16) float s_red[NWARPS][32];

    const int tid = threadIdx.x, warp = tid >> 5, lane = tid & 31;
    const int G = gridDim.x, cta = blockIdx.x;
    const int Lk = nb * BS;

    int ctx = ld_nc_i32(ctx_ptr);
    int chunk0 = 0, page0 = 0;
    if (warp >= NCONS) {
        chunk0 = (warp - NCONS) * G + cta;
        if (lane == 0 && (chunk0 >> 2) < nb) page0 = ld_nc_i32(bt + (chunk0 >> 2));
    }
    if (tid == 0) {
#pragma unroll
        for (int s = 0; s < NSTAGE; s++) {
            mbar_init(smem_u32(&s_full[s]), 1);
            mbar_init(smem_u32(&s_empty[s]), NCONS);
        }
        asm volatile("fence.mbarrier_init.release.cluster;" ::: "memory");
    }
    __syncthreads();
    ctx = min(max(ctx, 0), Lk);
    const int nchunks = (ctx + CH_TOK - 1) / CH_TOK;
    const uint32_t smem_base = smem_u32(smem);

    if (warp >= NCONS) {
        if (lane == 0) {
            const int s = warp - NCONS;
            const uint32_t full = smem_u32(&s_full[s]), empty = smem_u32(&s_empty[s]);
            const uint32_t dst = smem_base + s * STAGE_BYTES;
            int chunk = chunk0, page = page0;
            uint32_t ph = 0;
            while (true) {
                if (chunk >= nchunks) {
                    s_chunk[s] = -1;
                    mbar_arrive(full);
                    break;
                }
                s_chunk[s] = chunk;
                const size_t off = ((size_t)page * BS + (size_t)((chunk & 3) * CH_TOK)) * TOK_BYTES;
                mbar_expect_tx(full, STAGE_BYTES);
                bulk_g2s(dst, kc + off, CH_BYTES, full);
                bulk_g2s(dst + CH_BYTES, vc + off, CH_BYTES, full);
                mbar_wait(empty, ph);
                ph ^= 1;
                chunk = NSTAGE * G + (int)atomicAdd(&g_work, 1u);
                if (chunk < nchunks) page = ld_nc_i32(bt + (chunk >> 2));
            }
        }
        __syncwarp();
    } else {
        const int w = warp;
        uint32_t qf[8][2];
        {
            const int n = lane >> 2, h = lane >> 3;
            const uint32_t* qrow = reinterpret_cast<const uint32_t*>(q + (size_t)(8 * w + n) * DH);
#pragma unroll
            for (int j = 0; j < 8; j++) {
                const int d0 = 16 * (j ^ h) + (lane & 3) * 2;
                qf[j][0] = __ldg(qrow + (d0 >> 1));
                qf[j][1] = __ldg(qrow + ((d0 + 8) >> 1));
            }
        }
        uint32_t koff, voff;
        {
            const int mi = lane >> 3, r = lane & 7, h = r & 3;
            const int rhoK = r + 8 * (mi & 1), bK = mi >> 1;
            koff = (rhoK >> 2) * TOK_BYTES + (4 * w + h) * 256 + ((2 * h + bK) << 4);
            const int rhoV = r + 8 * (mi >> 1), bV = mi & 1;
            voff = CH_BYTES + (rhoV >> 2) * TOK_BYTES + (4 * w + h) * 256 + ((2 * h + bV) << 4);
        }
        const bool valid_lane = (((lane >> 2) & 3) == (lane & 3));
        const int tokA = lane >> 4;
        const int src0 = 5 * (lane & 3), src1 = src0 + 16;

        float acc[8][4];
#pragma unroll
        for (int i = 0; i < 8; i++) { acc[i][0] = acc[i][1] = acc[i][2] = acc[i][3] = 0.f; }
        float m0 = NEG_INIT, m1 = NEG_INIT, l0 = 0.f, l1 = 0.f;

        uint32_t dead = 0;
        uint32_t ph = 0;
        while (true) {
#pragma unroll 1
            for (int s = 0; s < NSTAGE; s++) {
                if (dead & (1u << s)) continue;
                mbar_wait(smem_u32(&s_full[s]), ph);
                const int chunk = *(volatile int*)&s_chunk[s];
                if (chunk < 0) { dead |= 1u << s; continue; }
                const uint32_t sb = smem_base + s * STAGE_BYTES;
                float c0[4] = {0.f, 0.f, 0.f, 0.f}, c1[4] = {0.f, 0.f, 0.f, 0.f};
                const uint32_t ka = sb + koff;
#pragma unroll
                for (int j = 0; j < 8; j += 2) {
                    uint32_t a[4], b[4];
                    ldsm4(a, ka ^ (j << 5));
                    ldsm4(b, ka ^ ((j + 1) << 5));
                    mma16816(c0, a, qf[j][0], qf[j][1]);
                    mma16816(c1, b, qf[j + 1][0], qf[j + 1][1]);
                }
                const int rem = ctx - chunk * CH_TOK;
                const bool vA = valid_lane && (tokA < rem), vB = valid_lane && (tokA + 2 < rem);
                const float NINF = __int_as_float(0xff800000);
                const float s0 = vA ? (c0[0] + c1[0]) * QK_SCALE : NINF;
                const float s1 = vA ? (c0[1] + c1[1]) * QK_SCALE : NINF;
                const float s2 = vB ? (c0[2] + c1[2]) * QK_SCALE : NINF;
                const float s3 = vB ? (c0[3] + c1[3]) * QK_SCALE : NINF;
                const float x0 = fmaxf(s0, s2), x1 = fmaxf(s1, s3);
                const float y0 = fmaxf(__shfl_sync(0xffffffffu, x0, src0), __shfl_sync(0xffffffffu, x0, src1));
                const float y1 = fmaxf(__shfl_sync(0xffffffffu, x1, src0), __shfl_sync(0xffffffffu, x1, src1));
                const float n0 = fmaxf(m0, y0), n1 = fmaxf(m1, y1);
                if (__any_sync(0xffffffffu, (n0 > m0) || (n1 > m1))) {
                    const float a0 = ex2(m0 - n0), a1 = ex2(m1 - n1);
                    l0 *= a0; l1 *= a1;
#pragma unroll
                    for (int i = 0; i < 8; i++) {
                        acc[i][0] *= a0; acc[i][1] *= a1; acc[i][2] *= a0; acc[i][3] *= a1;
                    }
                    m0 = n0; m1 = n1;
                }
                const float p0 = ex2(s0 - m0), p1 = ex2(s1 - m1), p2 = ex2(s2 - m0), p3 = ex2(s3 - m1);
                l0 += p0 + p2; l1 += p1 + p3;
                const uint32_t pb0 = movm(pack_bf16(p0, p1));
                const uint32_t pb1 = movm(pack_bf16(p2, p3));
                const uint32_t va = sb + voff;
#pragma unroll
                for (int i = 0; i < 8; i++) {
                    uint32_t a[4];
                    ldsm4t(a, va ^ (i << 5));
                    mma16816(acc[i], a, pb0, pb1);
                }
                __syncwarp();
                if (lane == 0) mbar_arrive(smem_u32(&s_empty[s]));
            }
            if (dead == (1u << NSTAGE) - 1u) break;
            ph ^= 1;
        }
#pragma unroll
        for (int o = 4; o < 32; o <<= 1) {
            l0 += __shfl_xor_sync(0xffffffffu, l0, o);
            l1 += __shfl_xor_sync(0xffffffffu, l1, o);
        }
        const int h = lane & 3;
        const int head0 = 8 * w + 2 * h;
        if (lane < 4) {
            g_part_ml[(size_t)head0 * MAXG + cta] = make_float2(m0, l0);
            g_part_ml[(size_t)(head0 + 1) * MAXG + cta] = make_float2(m1, l1);
        }
        float* po0 = g_part_o + ((size_t)head0 * MAXG + cta) * DH + (lane >> 2);
        float* po1 = po0 + (size_t)MAXG * DH;
#pragma unroll
        for (int i = 0; i < 8; i++) {
            const int d = 16 * (i ^ h);
            po0[d] = acc[i][0];
            po1[d] = acc[i][1];
            po0[d + 8] = acc[i][2];
            po1[d + 8] = acc[i][3];
        }
    }

    __syncthreads();
    if (tid == 0) {
        asm volatile("red.release.gpu.global.add.u32 [%0], 1;" ::"l"(&g_arrive) : "memory");
        uint32_t n = 0;
        while (true) {
            uint32_t v;
            asm volatile("ld.acquire.gpu.global.u32 %0, [%1];" : "=r"(v) : "l"(&g_arrive) : "memory");
            if (v >= (uint32_t)G) break;
            if (++n > (1u << 24)) __trap();
        }
    }
    __syncthreads();
    if (tid == 32) {
        const unsigned int e = atomicAdd(&g_exit, 1u);
        if (e == (unsigned)G - 1u) {
            g_work = 0; g_arrive = 0; g_exit = 0;
            __threadfence();
        }
    }

    if (cta < H * 4) {
        const int head = cta >> 2, qd = cta & 3;
        const int grp = tid >> 3, x = tid & 7;
        constexpr int NGRP = NTHREADS / 8;
        constexpr int NPASS = (MAXG + NGRP - 1) / NGRP;
        float4 v[NPASS];
        float mc[NPASS];
#pragma unroll
        for (int p = 0; p < NPASS; p++) {
            const int c = grp + p * NGRP;
            if (c < G) {
                v[p] = __ldcg(reinterpret_cast<const float4*>(g_part_o + ((size_t)head * MAXG + c) * DH + qd * 32 + x * 4));
                mc[p] = __ldcg(&g_part_ml[(size_t)head * MAXG + c].x);
            } else {
                v[p] = make_float4(0.f, 0.f, 0.f, 0.f);
                mc[p] = NEG_INIT;
            }
        }
        float2 ml[MAXG / 32];
        float M = NEG_INIT;
#pragma unroll
        for (int p = 0; p < MAXG / 32; p++) {
            const int c = lane + 32 * p;
            ml[p] = (c < G) ? __ldcg(&g_part_ml[(size_t)head * MAXG + c]) : make_float2(NEG_INIT, 0.f);
            M = fmaxf(M, ml[p].x);
        }
#pragma unroll
        for (int o = 16; o > 0; o >>= 1) M = fmaxf(M, __shfl_xor_sync(0xffffffffu, M, o));
        float L = 0.f;
#pragma unroll
        for (int p = 0; p < MAXG / 32; p++) L += ml[p].y * ex2(ml[p].x - M);
#pragma unroll
        for (int o = 16; o > 0; o >>= 1) L += __shfl_xor_sync(0xffffffffu, L, o);
        float4 a = make_float4(0.f, 0.f, 0.f, 0.f);
#pragma unroll
        for (int p = 0; p < NPASS; p++) {
            const float wgt = ex2(mc[p] - M);
            a.x += wgt * v[p].x; a.y += wgt * v[p].y; a.z += wgt * v[p].z; a.w += wgt * v[p].w;
        }
#pragma unroll
        for (int o = 8; o < 32; o <<= 1) {
            a.x += __shfl_xor_sync(0xffffffffu, a.x, o);
            a.y += __shfl_xor_sync(0xffffffffu, a.y, o);
            a.z += __shfl_xor_sync(0xffffffffu, a.z, o);
            a.w += __shfl_xor_sync(0xffffffffu, a.w, o);
        }
        if (lane < 8) *reinterpret_cast<float4*>(&s_red[warp][lane * 4]) = a;
        __syncthreads();
        if (warp == 0) {
            float r = 0.f;
#pragma unroll
            for (int k = 0; k < NWARPS; k++) r += s_red[k][lane];
            const int d = qd * 32 + lane;
            if (M < MASKED + 150.f) {
                const float Mall = fmaxf(M, MASKED);
                const float wa = ex2(M - Mall), wb = ex2(MASKED - Mall);
                float sv = 0.f;
                for (int t = ctx; t < Lk; t++) {
                    const int pg = bt[t >> 4];
                    const __nv_bfloat16* vp = reinterpret_cast<const __nv_bfloat16*>(
                        vc + ((size_t)pg * BS + (t & 15)) * TOK_BYTES) + (head >> 1) * DH + d;
                    sv += __bfloat162float(*vp);
                }
                r = wa * r + wb * sv;
                L = wa * L + wb * (float)(Lk - ctx);
            }
            out[head * DH + d] = __float2bfloat16(r / L);
        }
    }
}

}

extern "C" void kernel_launch(void* const* d_in, const int* in_sizes, int n_in, void* d_out, int out_size) {
    (void)n_in; (void)out_size;
    const __nv_bfloat16* q = (const __nv_bfloat16*)d_in[0];
    const uint8_t* kc = (const uint8_t*)d_in[1];
    const uint8_t* vc = (const uint8_t*)d_in[2];
    const int* bt = (const int*)d_in[3];
    const int* ctx = (const int*)d_in[4];
    __nv_bfloat16* out = (__nv_bfloat16*)d_out;
    const int B = in_sizes[4];
    const int nb = in_sizes[3] / B;

    static int grid = 0;
    if (grid == 0) {
        int dev = 0, sms = 0;
        cudaGetDevice(&dev);
        cudaDeviceGetAttribute(&sms, cudaDevAttrMultiProcessorCount, dev);
        cudaFuncSetAttribute(decode_kernel, cudaFuncAttributeMaxDynamicSharedMemorySize, SMEM_BYTES);
        grid = sms < MAXG ? sms : MAXG;
        if (grid < H * 4) grid = H * 4;
    }
    for (int b = 0; b < B; b++) {
        decode_kernel<<<grid, NTHREADS, SMEM_BYTES, cudaStreamPerThread>>>(
            q + (size_t)b * H * DH, kc, vc, bt + (size_t)b * nb, ctx + b, out + (size_t)b * H * DH, nb);
    }
}
```

```cpp
#include <cuda_runtime.h>
#include <cuda_bf16.h>
#include <stdint.h>

namespace {

constexpr int H = 32, HKV = 16, DH = 128, BS = 16;
constexpr int TOK_BYTES = HKV * DH * 2;
constexpr int CH_TOK = 4;
constexpr int CH_BYTES = CH_TOK * TOK_BYTES;
#define NCH_ 6
#define GATE_SLEEP0 400
#define GATE_K 48
constexpr int NCH = NCH_;
constexpr int NSLOT = 2 * NCH;
constexpr int NCONS = 4;
constexpr int NHELP = 8;
constexpr int NWARPS = NCONS + 1 + NHELP;
constexpr int NTHREADS = NWARPS * 32;
constexpr int MAXG = 160;
constexpr int NGRP = NHELP * 4;
constexpr int NPASS = MAXG / NGRP;
constexpr int SMEM_RING = NSLOT * CH_BYTES;
constexpr int MIN_SMEM = 120 * 1024;
constexpr int MAX_SMEM = (SMEM_RING > MIN_SMEM) ? SMEM_RING : MIN_SMEM;
static_assert(NSLOT <= NWARPS, "prologue issue uses one warp per slot");

constexpr float NEG_INIT = -1.0e30f;
constexpr float LOG2E = 1.4426950408889634f;
constexpr float QK_SCALE = 0.08838834764831845f * LOG2E;
constexpr float MASKED = -998244352.0f * LOG2E;

__device__ uint2 g_rec[H * 4 * MAXG * 8];
__device__ uint2 g_ml[MAXG * H];
__device__ unsigned int g_epoch;
__device__ unsigned int g_cnt[2][3 * 32];

#define TS(i) do {} while (0)

__device__ __forceinline__ uint32_t smem_u32(const void* p) { return (uint32_t)__cvta_generic_to_shared(p); }
__device__ __forceinline__ void mbar_init(uint32_t bar, int cnt) {
    asm volatile("mbarrier.init.shared::cta.b64 [%0], %1;" ::"r"(bar), "r"(cnt) : "memory");
}
__device__ __forceinline__ void mbar_expect_tx(uint32_t bar, uint32_t bytes) {
    asm volatile("mbarrier.arrive.expect_tx.shared::cta.b64 _, [%0], %1;" ::"r"(bar), "r"(bytes) : "memory");
}
__device__ __forceinline__ void mbar_arrive(uint32_t bar) {
    asm volatile("mbarrier.arrive.shared::cta.b64 _, [%0];" ::"r"(bar) : "memory");
}
__device__ __forceinline__ bool mbar_try(uint32_t bar, uint32_t parity) {
    uint32_t ok;
    asm volatile(
        "{\n.reg .pred p;\n"
        "mbarrier.try_wait.parity.shared::cta.b64 p, [%1], %2;\n"
        "selp.u32 %0, 1, 0, p;\n}"
        : "=r"(ok) : "r"(bar), "r"(parity) : "memory");
    return ok != 0;
}
__device__ __forceinline__ void mbar_wait(uint32_t bar, uint32_t parity) {
    if (mbar_try(bar, parity)) return;
    uint32_t n = 0;
    while (!mbar_try(bar, parity)) {
        if (++n > (1u << 24)) __trap();
    }
}
__device__ __forceinline__ void bulk_g2s(uint32_t dst, const void* src, uint32_t bytes, uint32_t bar) {
    asm volatile("cp.async.bulk.shared::cluster.global.mbarrier::complete_tx::bytes [%0], [%1], %2, [%3];"
                 ::"r"(dst), "l"(src), "r"(bytes), "r"(bar) : "memory");
}
__device__ __forceinline__ void bulk_g2s_ef(uint32_t dst, const void* src, uint32_t bytes, uint32_t bar, uint64_t pol) {
    asm volatile("cp.async.bulk.shared::cluster.global.mbarrier::complete_tx::bytes.L2::cache_hint [%0], [%1], %2, [%3], %4;"
                 ::"r"(dst), "l"(src), "r"(bytes), "r"(bar), "l"(pol) : "memory");
}
__device__ __forceinline__ uint64_t policy_evict_first() {
    uint64_t pol;
    asm volatile("createpolicy.fractional.L2::evict_first.b64 %0, 1.0;" : "=l"(pol));
    return pol;
}
__device__ __forceinline__ void ldsm4(uint32_t (&r)[4], uint32_t addr) {
    asm volatile("ldmatrix.sync.aligned.m8n8.x4.shared.b16 {%0,%1,%2,%3}, [%4];"
                 : "=r"(r[0]), "=r"(r[1]), "=r"(r[2]), "=r"(r[3]) : "r"(addr) : "memory");
}
__device__ __forceinline__ void ldsm4t(uint32_t (&r)[4], uint32_t addr) {
    asm volatile("ldmatrix.sync.aligned.m8n8.x4.trans.shared.b16 {%0,%1,%2,%3}, [%4];"
                 : "=r"(r[0]), "=r"(r[1]), "=r"(r[2]), "=r"(r[3]) : "r"(addr) : "memory");
}
__device__ __forceinline__ void mma16816(float (&c)[4], const uint32_t (&a)[4], uint32_t b0, uint32_t b1) {
    asm volatile("mma.sync.aligned.m16n8k16.row.col.f32.bf16.bf16.f32 {%0,%1,%2,%3}, {%4,%5,%6,%7}, {%8,%9}, {%0,%1,%2,%3};"
                 : "+f"(c[0]), "+f"(c[1]), "+f"(c[2]), "+f"(c[3])
                 : "r"(a[0]), "r"(a[1]), "r"(a[2]), "r"(a[3]), "r"(b0), "r"(b1));
}
__device__ __forceinline__ uint32_t movm(uint32_t a) {
    uint32_t d;
    asm volatile("movmatrix.sync.aligned.m8n8.trans.b16 %0, %1;" : "=r"(d) : "r"(a));
    return d;
}
__device__ __forceinline__ uint32_t pack_bf16(float lo, float hi) {
    uint32_t d;
    asm("cvt.rn.bf16x2.f32 %0, %1, %2;" : "=r"(d) : "f"(hi), "f"(lo));
    return d;
}
__device__ __forceinline__ float ex2(float x) {
    float y;
    asm("ex2.approx.ftz.f32 %0, %1;" : "=f"(y) : "f"(x));
    return y;
}
__device__ __forceinline__ int ld_nc_i32(const int* p) {
    int v;
    asm volatile("ld.global.nc.s32 %0, [%1];" : "=r"(v) : "l"(p));
    return v;
}
__device__ __forceinline__ uint32_t nz(float f) {
    const uint32_t u = __float_as_uint(f);
    return u == 0u ? 0x80000000u : u;
}
__device__ __forceinline__ void st4(uint4* p, uint32_t a, uint32_t b, uint32_t c, uint32_t d) {
    asm volatile("st.relaxed.gpu.global.v4.u32 [%0], {%1,%2,%3,%4};" ::"l"(p), "r"(a), "r"(b), "r"(c), "r"(d) : "memory");
}
__device__ __forceinline__ void st4v(void* p, uint32_t a, uint32_t b, uint32_t c, uint32_t d) {
    asm volatile("st.relaxed.gpu.global.v4.u32 [%0], {%1,%2,%3,%4};" ::"l"(p), "r"(a), "r"(b), "r"(c), "r"(d) : "memory");
}
__device__ __forceinline__ uint32_t nzu(uint32_t u) { return u == 0u ? 0x80000000u : u; }
__device__ __forceinline__ void st4_pred(uint4* p, uint32_t a, uint32_t b, uint32_t c, uint32_t d, int pred) {
    asm volatile("{\n.reg .pred p;\nsetp.ne.s32 p, %5, 0;\n@p st.relaxed.gpu.global.v4.u32 [%0], {%1,%2,%3,%4};\n}"
                 ::"l"(p), "r"(a), "r"(b), "r"(c), "r"(d), "r"(pred) : "memory");
}
__device__ __forceinline__ void st2_pred(uint2* p, uint32_t a, uint32_t b, int pred) {
    asm volatile("{\n.reg .pred p;\nsetp.ne.s32 p, %3, 0;\n@p st.relaxed.gpu.global.v2.u32 [%0], {%1,%2};\n}"
                 ::"l"(p), "r"(a), "r"(b), "r"(pred) : "memory");
}
__device__ __forceinline__ void ld4_pred(uint4& v, const uint4* p, int pred) {
    asm volatile("{\n.reg .pred p;\nsetp.ne.s32 p, %5, 0;\n@p ld.relaxed.gpu.global.v4.u32 {%0,%1,%2,%3}, [%4];\n}"
                 : "+r"(v.x), "+r"(v.y), "+r"(v.z), "+r"(v.w) : "l"(p), "r"(pred) : "memory");
}
__device__ __forceinline__ void ld2_pred(uint2& v, const uint2* p, int pred) {
    asm volatile("{\n.reg .pred p;\nsetp.ne.s32 p, %3, 0;\n@p ld.relaxed.gpu.global.v2.u32 {%0,%1}, [%2];\n}"
                 : "+r"(v.x), "+r"(v.y) : "l"(p), "r"(pred) : "memory");
}
__device__ __forceinline__ void named_bar(int id, int n) {
    asm volatile("bar.sync %0, %1;" ::"r"(id), "r"(n) : "memory");
}

__global__ void __launch_bounds__(NTHREADS, 1)
decode_kernel(const __nv_bfloat16* __restrict__ q, const uint8_t* __restrict__ kc, const uint8_t* __restrict__ vc,
              const int* __restrict__ bt, const int* __restrict__ ctx_ptr, __nv_bfloat16* __restrict__ out,
              int nb, int npass)
{
    extern __shared__ __align__(1024) uint8_t smem[];
    __shared__ __align__(8) uint64_t s_full[NSLOT], s_empty[NSLOT], s_done, s_clr;
    __shared__ int s_chunk[NCH];
    __shared__ unsigned int s_epoch;
    __shared__ __align__(16) float s_red[NHELP][32];
    __shared__ float2 s_ml[NHELP];

    const int tid = threadIdx.x, warp = tid >> 5, lane = tid & 31;
    const int G = gridDim.x, cta = blockIdx.x;
    const int Lk = nb * BS;
    const uint32_t smem_base = smem_u32(smem);

    if (tid == 0) TS(0);
    int ctx = ld_nc_i32(ctx_ptr);
    if (lane == 0) {
        if (warp < NSLOT) {
            const int s = warp;
            const int ch = (s >> 1) * G + cta;
            const bool fill = s < NSLOT - 2;
            const int page = (fill && (ch >> 2) < nb) ? ld_nc_i32(bt + (ch >> 2)) : 0;
            const uint32_t fb = smem_u32(&s_full[s]);
            mbar_init(fb, 1);
            mbar_init(smem_u32(&s_empty[s]), NCONS);
            asm volatile("fence.mbarrier_init.release.cluster;" ::: "memory");
            const int cx = min(max(ctx, 0), Lk);
            if (fill) {
                if (ch * CH_TOK < cx) {
                    const size_t off = ((size_t)page * BS + (size_t)((ch & 3) * CH_TOK)) * TOK_BYTES;
                    mbar_expect_tx(fb, CH_BYTES);
                    bulk_g2s_ef(smem_base + s * CH_BYTES, ((s & 1) ? vc : kc) + off, CH_BYTES, fb, policy_evict_first());
                    if (!(s & 1)) s_chunk[s >> 1] = ch;
                } else if (!(s & 1)) {
                    s_chunk[s >> 1] = -1;
                    mbar_arrive(fb);
                }
            }
            if (s == 0) TS(1);
        }
        if (warp == NWARPS - 1) {
            mbar_init(smem_u32(&s_done), NCONS);
            mbar_init(smem_u32(&s_clr), NHELP);
            asm volatile("fence.mbarrier_init.release.cluster;" ::: "memory");
        }
    }
    unsigned int nxt = 0;
    unsigned int* cnt = nullptr;
    if (tid == NCONS * 32) {
        unsigned int epoch;
        asm volatile("ld.relaxed.gpu.global.u32 %0, [%1];" : "=r"(epoch) : "l"(&g_epoch) : "memory");
        s_epoch = epoch;
        cnt = g_cnt[epoch & 1];
        nxt = atomicAdd(cnt, 1u);
        if (cta == 0) { unsigned int* o = g_cnt[(epoch & 1) ^ 1]; o[0] = 0; o[32] = 0; o[64] = 0; }
    }
    ctx = min(max(ctx, 0), Lk);
    const int nchunks = (ctx + CH_TOK - 1) / CH_TOK;

    if (warp == NCONS) {
        __syncwarp();
        asm volatile("bar.arrive 3, %0;" ::"r"(NTHREADS) : "memory");
        named_bar(0, NTHREADS);
        if (lane == 0) {
            {
                int j = NCH - 1;
                uint32_t ph = 1;
                const uint64_t pol = policy_evict_first();
                int ch = (NCH - 1) * G + cta;
                while (true) {
                    const uint32_t fK = smem_u32(&s_full[2 * j]), fV = fK + 8;
                    const uint32_t eK = smem_u32(&s_empty[2 * j]), eV = eK + 8;
                    if (ch >= nchunks) {
                        mbar_wait(eK, ph);
                        s_chunk[j] = -1;
                        mbar_arrive(fK);
                        break;
                    }
                    const int page = ld_nc_i32(bt + (ch >> 2));
                    const size_t off = ((size_t)page * BS + (size_t)((ch & 3) * CH_TOK)) * TOK_BYTES;
                    const uint32_t dst = smem_base + (2 * j) * CH_BYTES;
                    mbar_wait(eK, ph);
                    s_chunk[j] = ch;
                    mbar_expect_tx(fK, CH_BYTES);
                    bulk_g2s_ef(dst, kc + off, CH_BYTES, fK, pol);
                    mbar_wait(eV, ph);
                    mbar_expect_tx(fV, CH_BYTES);
                    bulk_g2s_ef(dst + CH_BYTES, vc + off, CH_BYTES, fV, pol);
                    if (++j == NCH) { j = 0; ph ^= 1; }
                    ch = NCH * G + (int)nxt;
                    if (ch < nchunks) nxt = atomicAdd(cnt, 1u);
                }
            }
            mbar_wait(smem_u32(&s_done), 0);
            TS(8);
            asm volatile("red.relaxed.gpu.global.add.u32 [%0], 1;" ::"l"(cnt + 32) : "memory");
        }
    } else if (warp < NCONS) {
        const int w = warp;
        uint32_t qf[8][2];
        {
            const int n = lane >> 2, h = lane >> 3;
            const uint32_t* qrow = reinterpret_cast<const uint32_t*>(q + (size_t)(8 * w + n) * DH);
#pragma unroll
            for (int j = 0; j < 8; j++) {
                const int d0 = 16 * (j ^ h) + (lane & 3) * 2;
                qf[j][0] = __ldg(qrow + (d0 >> 1));
                qf[j][1] = __ldg(qrow + ((d0 + 8) >> 1));
            }
        }
        uint32_t koff, voff;
        {
            const int mi = lane >> 3, r = lane & 7, h = r & 3;
            const int rhoK = r + 8 * (mi & 1), bK = mi >> 1;
            koff = (rhoK >> 2) * TOK_BYTES + (4 * w + h) * 256 + ((2 * h + bK) << 4);
            const int rhoV = r + 8 * (mi >> 1), bV = mi & 1;
            voff = CH_BYTES + (rhoV >> 2) * TOK_BYTES + (4 * w + h) * 256 + ((2 * h + bV) << 4);
        }
        const bool valid_lane = (((lane >> 2) & 3) == (lane & 3));
        const int tokA = lane >> 4;
        const int src0 = 5 * (lane & 3), src1 = src0 + 16;

        float acc[8][4];
#pragma unroll
        for (int i = 0; i < 8; i++) { acc[i][0] = acc[i][1] = acc[i][2] = acc[i][3] = 0.f; }
        float m0 = NEG_INIT, m1 = NEG_INIT, l0 = 0.f, l1 = 0.f;
        __syncwarp();
        asm volatile("bar.arrive 0, %0;" ::"r"(NTHREADS) : "memory");

#pragma unroll 1
        for (int pass = 0; pass < npass; pass++) {
            {
                int j = 0;
                uint32_t ph = 0;
                while (true) {
                    const uint32_t fK = smem_u32(&s_full[2 * j]), eK = smem_u32(&s_empty[2 * j]);
                    int chunk = 0;
                    if (pass) {
                        mbar_wait(fK, ph);
                        chunk = *(volatile int*)&s_chunk[j];
                    }
                    if (chunk < 0) break;
                    const uint32_t sb = smem_base + (2 * j) * CH_BYTES;
                    float c0[4] = {0.f, 0.f, 0.f, 0.f}, c1[4] = {0.f, 0.f, 0.f, 0.f};
                    const uint32_t ka = sb + koff;
                    {
                        uint32_t a[8][4];
#pragma unroll
                        for (int jj = 0; jj < 8; jj++) ldsm4(a[jj], ka ^ (jj << 5));
                        __syncwarp();
                        if (pass && lane == 0) mbar_arrive(eK);
#pragma unroll
                        for (int jj = 0; jj < 8; jj += 2) {
                            mma16816(c0, a[jj], qf[jj][0], qf[jj][1]);
                            mma16816(c1, a[jj + 1], qf[jj + 1][0], qf[jj + 1][1]);
                        }
                    }
                    uint32_t av[8][4];
                    if (pass) mbar_wait(fK + 8, ph);
                    {
                        const uint32_t va = sb + voff;
#pragma unroll
                        for (int i = 0; i < 8; i++) ldsm4t(av[i], va ^ (i << 5));
                        __syncwarp();
                        if (pass && lane == 0) mbar_arrive(eK + 8);
                    }
                    const int rem = ctx - chunk * CH_TOK;
                    const bool vA = valid_lane && (tokA < rem), vB = valid_lane && (tokA + 2 < rem);
                    const float NINF = __int_as_float(0xff800000);
                    const float s0 = vA ? (c0[0] + c1[0]) * QK_SCALE : NINF;
                    const float s1 = vA ? (c0[1] + c1[1]) * QK_SCALE : NINF;
                    const float s2 = vB ? (c0[2] + c1[2]) * QK_SCALE : NINF;
                    const float s3 = vB ? (c0[3] + c1[3]) * QK_SCALE : NINF;
                    const float x0 = fmaxf(s0, s2), x1 = fmaxf(s1, s3);
                    const float y0 = fmaxf(__shfl_sync(0xffffffffu, x0, src0), __shfl_sync(0xffffffffu, x0, src1));
                    const float y1 = fmaxf(__shfl_sync(0xffffffffu, x1, src0), __shfl_sync(0xffffffffu, x1, src1));
                    const float n0 = fmaxf(m0, y0), n1 = fmaxf(m1, y1);
                    if (__any_sync(0xffffffffu, (n0 > m0) || (n1 > m1))) {
                        const float a0 = ex2(m0 - n0), a1 = ex2(m1 - n1);
                        l0 *= a0; l1 *= a1;
#pragma unroll
                        for (int i = 0; i < 8; i++) {
                            acc[i][0] *= a0; acc[i][1] *= a1; acc[i][2] *= a0; acc[i][3] *= a1;
                        }
                        m0 = n0; m1 = n1;
                    }
                    const float p0 = ex2(s0 - m0), p1 = ex2(s1 - m1), p2 = ex2(s2 - m0), p3 = ex2(s3 - m1);
                    l0 += p0 + p2; l1 += p1 + p3;
                    const uint32_t pb0 = movm(pack_bf16(p0, p1));
                    const uint32_t pb1 = movm(pack_bf16(p2, p3));
#pragma unroll
                    for (int i = 0; i < 8; i++) mma16816(acc[i], av[i], pb0, pb1);
                    if (!pass) break;
                    if (++j == NCH) { j = 0; ph ^= 1; }
                }
                if (tid == 0 && pass) TS(3);
            }
            const int h = lane & 3, g = lane >> 2;
            const int rec0 = ((8 * w + 2 * h) * 4) * MAXG + cta;
            if (pass) mbar_wait(smem_u32(&s_clr), 0);
            const float r0 = __shfl_sync(0xffffffffu, l0, src0) + __shfl_sync(0xffffffffu, l0, src1);
            const float r1 = __shfl_sync(0xffffffffu, l1, src0) + __shfl_sync(0xffffffffu, l1, src1);
            st4_pred(reinterpret_cast<uint4*>(g_ml + cta * H + 8 * w + 2 * h), nz(m0), nz(r0), nz(m1), nz(r1), pass && lane < 4);
#pragma unroll
            for (int i0 = 0; i0 < 8; i0 += 2) {
                const int qd = (i0 >> 1) ^ (h >> 1);
                uint2* p = g_rec + (size_t)(rec0 + qd * MAXG) * 8 + g;
                st2_pred(p, nzu(pack_bf16(acc[i0][0], acc[i0][2])), nzu(pack_bf16(acc[i0 + 1][0], acc[i0 + 1][2])), pass);
                st2_pred(p + (size_t)4 * MAXG * 8, nzu(pack_bf16(acc[i0][1], acc[i0][3])), nzu(pack_bf16(acc[i0 + 1][1], acc[i0 + 1][3])), pass);
            }
            __syncwarp();
            if (pass && lane == 0) mbar_arrive(smem_u32(&s_done));
            if (!pass) {
#pragma unroll
                for (int i = 0; i < 8; i++) { acc[i][0] = acc[i][1] = acc[i][2] = acc[i][3] = 0.f; }
                m0 = NEG_INIT; m1 = NEG_INIT; l0 = 0.f; l1 = 0.f;
                named_bar(3, NTHREADS);
            }
        }
        if (tid == 0) TS(4);
    } else {
        const int hw = warp - NCONS - 1;
        const int t = tid - (NCONS + 1) * 32;
        const int grp = t >> 3, x = t & 7;
        __syncwarp();
        asm volatile("bar.arrive 3, %0;" ::"r"(NTHREADS) : "memory");
        named_bar(0, NTHREADS);
        const unsigned int epoch = s_epoch;
        unsigned int* cnt = g_cnt[epoch & 1];
        for (int i = t; i < H * 4 * 4; i += NHELP * 32)
            st4v(g_rec + ((size_t)(i >> 2) * MAXG + cta) * 8 + (i & 3) * 2, 0u, 0u, 0u, 0u);
        if (t < 16) st4v(g_ml + cta * H + 2 * t, 0u, 0u, 0u, 0u);
        __syncwarp();
        if (lane == 0) {
            asm volatile("red.release.gpu.global.add.u32 [%0], 1;" ::"l"(cnt + 64) : "memory");
            asm volatile("fence.acq_rel.gpu;" ::: "memory");
            mbar_arrive(smem_u32(&s_clr));
        }
#pragma unroll 1
        for (int pass = 0; pass < npass; pass++) {
            if (pass && t == 0 && cta < H * 4) {
                uint32_t n = 0;
                while (true) {
                    unsigned int u;
                    asm volatile("ld.acquire.gpu.global.u32 %0, [%1];" : "=r"(u) : "l"(cnt + 64) : "memory");
                    if (u >= (unsigned)(NHELP * G)) break;
                    if (++n > (1u << 24)) __trap();
                    __nanosleep(500);
                }
                if (cta == 0) g_epoch = epoch + 1;
                const unsigned int target = (G > GATE_K) ? (unsigned)(G - GATE_K) : 0u;
                n = 0;
                while (true) {
                    unsigned int v;
                    asm volatile("ld.relaxed.gpu.global.u32 %0, [%1];" : "=r"(v) : "l"(cnt + 32) : "memory");
                    if (v >= target) break;
                    if (++n > (1u << 24)) __trap();
                    __nanosleep(v == 0 ? GATE_SLEEP0 : 0);
                }
                TS(5);
            }
            named_bar(1, NHELP * 32);
            if (cta >= H * 4) continue;

            const uint2* rp = g_rec + (size_t)cta * MAXG * 8 + x;
            const uint2* mp = g_ml + (cta >> 2);
            uint2 v[NPASS];
            uint2 ml[NPASS];
            uint32_t pend = 0;
#pragma unroll
            for (int p = 0; p < NPASS; p++) {
                v[p] = make_uint2(0x80000000u, 0x80000000u);
                ml[p] = make_uint2(__float_as_uint(NEG_INIT), 0x80000000u);
                if (pass && grp + p * NGRP < G) pend |= 1u << p;
            }
            uint32_t n = 0;
            do {
#pragma unroll
                for (int p = 0; p < NPASS; p++) {
                    const int c = grp + p * NGRP;
                    ld2_pred(v[p], rp + c * 8, pend & (1u << p));
                    ld2_pred(ml[p], mp + c * H, pend & (1u << p));
                }
#pragma unroll
                for (int p = 0; p < NPASS; p++) {
                    const bool ok = v[p].x && v[p].y && ml[p].x && ml[p].y;
                    if (ok) pend &= ~(1u << p);
                }
                if (++n > (1u << 22)) __trap();
            } while (pend);

            __syncwarp();
            float Mw = NEG_INIT;
#pragma unroll
            for (int p = 0; p < NPASS; p++) Mw = fmaxf(Mw, __uint_as_float(ml[p].x));
            Mw = fmaxf(Mw, __shfl_xor_sync(0xffffffffu, Mw, 8));
            Mw = fmaxf(Mw, __shfl_xor_sync(0xffffffffu, Mw, 16));
            float a0 = 0.f, a1 = 0.f, a2 = 0.f, a3 = 0.f, al = 0.f;
#pragma unroll
            for (int p = 0; p < NPASS; p++) {
                const float wgt = ex2(__uint_as_float(ml[p].x) - Mw);
                a0 += wgt * __uint_as_float(v[p].x << 16); a1 += wgt * __uint_as_float(v[p].x & 0xffff0000u);
                a2 += wgt * __uint_as_float(v[p].y << 16); a3 += wgt * __uint_as_float(v[p].y & 0xffff0000u);
                al += wgt * __uint_as_float(ml[p].y);
            }
#pragma unroll
            for (int o = 8; o < 32; o <<= 1) {
                a0 += __shfl_xor_sync(0xffffffffu, a0, o);
                a1 += __shfl_xor_sync(0xffffffffu, a1, o);
                a2 += __shfl_xor_sync(0xffffffffu, a2, o);
                a3 += __shfl_xor_sync(0xffffffffu, a3, o);
                al += __shfl_xor_sync(0xffffffffu, al, o);
            }
            if (lane < 8) *reinterpret_cast<float4*>(&s_red[hw][lane * 4]) = make_float4(a0, a1, a2, a3);
            if (lane == 0) s_ml[hw] = make_float2(Mw, al);
            named_bar(1, NHELP * 32);
            if (hw == 0) {
                float M = NEG_INIT;
                float2 wml[NHELP];
#pragma unroll
                for (int k = 0; k < NHELP; k++) { wml[k] = s_ml[k]; M = fmaxf(M, wml[k].x); }
                float r = 0.f, L = 0.f;
#pragma unroll
                for (int k = 0; k < NHELP; k++) {
                    const float wgt = ex2(wml[k].x - M);
                    r += wgt * s_red[k][lane];
                    L += wgt * wml[k].y;
                }
                const int head = cta >> 2, qd = cta & 3, h = (head >> 1) & 3;
                const int d = qd * 32 + 16 * (((lane >> 1) & 1) ^ (h & 1)) + 8 * (lane & 1) + (lane >> 2);
                if (pass && M < MASKED + 150.f) {
                    const float Mall = fmaxf(M, MASKED);
                    const float wa = ex2(M - Mall), wb = ex2(MASKED - Mall);
                    float sv = 0.f;
                    for (int tk = ctx; tk < Lk; tk++) {
                        const int pg = bt[tk >> 4];
                        const __nv_bfloat16* vp = reinterpret_cast<const __nv_bfloat16*>(
                            vc + ((size_t)pg * BS + (tk & 15)) * TOK_BYTES) + (head >> 1) * DH + d;
                        sv += __bfloat162float(*vp);
                    }
                    r = wa * r + wb * sv;
                    L = wa * L + wb * (float)(Lk - ctx);
                }
                const __nv_bfloat16 o = __float2bfloat16(__fdividef(r, L));
                if (pass) out[head * DH + d] = o;
                if (pass && t == 0) TS(6);
            }
        }
    }
}

}

extern "C" void kernel_launch(void* const* d_in, const int* in_sizes, int n_in, void* d_out, int out_size) {
    (void)n_in; (void)out_size;
    const __nv_bfloat16* q = (const __nv_bfloat16*)d_in[0];
    const uint8_t* kc = (const uint8_t*)d_in[1];
    const uint8_t* vc = (const uint8_t*)d_in[2];
    const int* bt = (const int*)d_in[3];
    const int* ctx = (const int*)d_in[4];
    __nv_bfloat16* out = (__nv_bfloat16*)d_out;
    const int B = in_sizes[4];
    const int nb = in_sizes[3] / B;

    static int grid = 0;
    if (grid == 0) {
        int dev = 0, sms = 0;
        cudaGetDevice(&dev);
        cudaDeviceGetAttribute(&sms, cudaDevAttrMultiProcessorCount, dev);
        cudaFuncSetAttribute(decode_kernel, cudaFuncAttributeMaxDynamicSharedMemorySize, MAX_SMEM);
        grid = sms < MAXG ? sms : MAXG;
        if (grid < H * 4) grid = H * 4;
    }
    for (int b = 0; b < B; b++) {
        decode_kernel<<<grid, NTHREADS, MAX_SMEM, cudaStreamPerThread>>>(
            q + (size_t)b * H * DH, kc, vc, bt + (size_t)b * nb, ctx + b, out + (size_t)b * H * DH, nb, 2);
    }
}
```

```cpp
#include <cuda_runtime.h>
#include <cuda.h>
#include <cuda_bf16.h>
#include <stdint.h>
#include <string.h>

namespace {

constexpr int H = 32, HKV = 16, DH = 128, BS = 16;
constexpr int TOK_BYTES = HKV * DH * 2;
constexpr int CH_TOK = 4;
constexpr int CH_BYTES = CH_TOK * TOK_BYTES;
#define NCH_ 7
#define GATE_SLEEP0 400
#define GATE_K 96
constexpr int NCH = NCH_;
constexpr int NSLOT = 2 * NCH;
constexpr int NCONS = 4;
constexpr int NHELP = 8;
constexpr int NWARPS = NCONS + 1 + NHELP;
constexpr int NTHREADS = NWARPS * 32;
constexpr int MAXG = 160;
constexpr int NGRP = NHELP * 4;
constexpr int NPASS = MAXG / NGRP;
constexpr int SMEM_RING = NSLOT * CH_BYTES;
constexpr int MIN_SMEM = 120 * 1024;
constexpr int MAX_SMEM = (SMEM_RING > MIN_SMEM) ? SMEM_RING : MIN_SMEM;
static_assert(NSLOT - 2 <= NWARPS, "prologue issue uses one warp per slot");

constexpr float NEG_INIT = -1.0e30f;
constexpr float LOG2E = 1.4426950408889634f;
constexpr float QK_SCALE = 0.08838834764831845f * LOG2E;
constexpr float MASKED = -998244352.0f * LOG2E;

__device__ uint2 g_rec[H * 4 * MAXG * 8];
__device__ uint2 g_ml[MAXG * H];
__device__ unsigned int g_epoch;
__device__ unsigned int g_cnt[2][3 * 32];

#define TS(i) do {} while (0)

__device__ __forceinline__ uint32_t smem_u32(const void* p) { return (uint32_t)__cvta_generic_to_shared(p); }
__device__ __forceinline__ void mbar_init(uint32_t bar, int cnt) {
    asm volatile("mbarrier.init.shared::cta.b64 [%0], %1;" ::"r"(bar), "r"(cnt) : "memory");
}
__device__ __forceinline__ void mbar_expect_tx(uint32_t bar, uint32_t bytes) {
    asm volatile("mbarrier.arrive.expect_tx.shared::cta.b64 _, [%0], %1;" ::"r"(bar), "r"(bytes) : "memory");
}
__device__ __forceinline__ void mbar_arrive(uint32_t bar) {
    asm volatile("mbarrier.arrive.shared::cta.b64 _, [%0];" ::"r"(bar) : "memory");
}
__device__ __forceinline__ bool mbar_try(uint32_t bar, uint32_t parity) {
    uint32_t ok;
    asm volatile(
        "{\n.reg .pred p;\n"
        "mbarrier.try_wait.parity.shared::cta.b64 p, [%1], %2;\n"
        "selp.u32 %0, 1, 0, p;\n}"
        : "=r"(ok) : "r"(bar), "r"(parity) : "memory");
    return ok != 0;
}
__device__ __forceinline__ void mbar_wait(uint32_t bar, uint32_t parity) {
    if (mbar_try(bar, parity)) return;
    uint32_t n = 0;
    while (!mbar_try(bar, parity)) {
        if (++n > (1u << 24)) __trap();
    }
}
__device__ __forceinline__ bool mbar_test(uint32_t bar, uint32_t parity) {
    uint32_t ok;
    asm volatile(
        "{\n.reg .pred p;\n"
        "mbarrier.test_wait.parity.shared::cta.b64 p, [%1], %2;\n"
        "selp.u32 %0, 1, 0, p;\n}"
        : "=r"(ok) : "r"(bar), "r"(parity) : "memory");
    return ok != 0;
}
__device__ __forceinline__ void mbar_spin(uint32_t bar, uint32_t parity) {
    uint32_t n = 0;
    while (!mbar_test(bar, parity)) {
        if (++n > (1u << 30)) __trap();
    }
}
#define PROD_WAIT mbar_wait
#define CONS_WAIT mbar_wait
__device__ __forceinline__ void bulk_g2s(uint32_t dst, const void* src, uint32_t bytes, uint32_t bar) {
    asm volatile("cp.async.bulk.shared::cluster.global.mbarrier::complete_tx::bytes [%0], [%1], %2, [%3];"
                 ::"r"(dst), "l"(src), "r"(bytes), "r"(bar) : "memory");
}
__device__ __forceinline__ void bulk_g2s_ef(uint32_t dst, const void* src, uint32_t bytes, uint32_t bar, uint64_t pol) {
    asm volatile("cp.async.bulk.shared::cluster.global.mbarrier::complete_tx::bytes.L2::cache_hint [%0], [%1], %2, [%3], %4;"
                 ::"r"(dst), "l"(src), "r"(bytes), "r"(bar), "l"(pol) : "memory");
}
__device__ __forceinline__ void load_chunk(bool tmap, uint32_t dst, const CUtensorMap* tm, const uint8_t* base,
                                           int page, int ch, uint32_t bar, uint64_t pol) {
    if (tmap) {
        asm volatile("cp.async.bulk.tensor.4d.shared::cluster.global.mbarrier::complete_tx::bytes.L2::cache_hint "
                     "[%0], [%1, {%3, %4, %5, %6}], [%2], %7;"
                     ::"r"(dst), "l"(tm), "r"(bar), "r"(0), "r"((ch & 3) * CH_TOK), "r"(0), "r"(page), "l"(pol) : "memory");
    } else {
        const size_t off = ((size_t)page * BS + (size_t)((ch & 3) * CH_TOK)) * TOK_BYTES;
        bulk_g2s_ef(dst, base + off, CH_BYTES, bar, pol);
    }
}
__device__ __forceinline__ uint64_t policy_evict_first() {
    uint64_t pol;
    asm volatile("createpolicy.fractional.L2::evict_first.b64 %0, 1.0;" : "=l"(pol));
    return pol;
}
__device__ __forceinline__ void ldsm4(uint32_t (&r)[4], uint32_t addr) {
    asm volatile("ldmatrix.sync.aligned.m8n8.x4.shared.b16 {%0,%1,%2,%3}, [%4];"
                 : "=r"(r[0]), "=r"(r[1]), "=r"(r[2]), "=r"(r[3]) : "r"(addr) : "memory");
}
__device__ __forceinline__ void ldsm4t(uint32_t (&r)[4], uint32_t addr) {
    asm volatile("ldmatrix.sync.aligned.m8n8.x4.trans.shared.b16 {%0,%1,%2,%3}, [%4];"
                 : "=r"(r[0]), "=r"(r[1]), "=r"(r[2]), "=r"(r[3]) : "r"(addr) : "memory");
}
__device__ __forceinline__ void mma16816(float (&c)[4], const uint32_t (&a)[4], uint32_t b0, uint32_t b1) {
    asm volatile("mma.sync.aligned.m16n8k16.row.col.f32.bf16.bf16.f32 {%0,%1,%2,%3}, {%4,%5,%6,%7}, {%8,%9}, {%0,%1,%2,%3};"
                 : "+f"(c[0]), "+f"(c[1]), "+f"(c[2]), "+f"(c[3])
                 : "r"(a[0]), "r"(a[1]), "r"(a[2]), "r"(a[3]), "r"(b0), "r"(b1));
}
__device__ __forceinline__ uint32_t movm(uint32_t a) {
    uint32_t d;
    asm volatile("movmatrix.sync.aligned.m8n8.trans.b16 %0, %1;" : "=r"(d) : "r"(a));
    return d;
}
__device__ __forceinline__ uint32_t pack_bf16(float lo, float hi) {
    uint32_t d;
    asm("cvt.rn.bf16x2.f32 %0, %1, %2;" : "=r"(d) : "f"(hi), "f"(lo));
    return d;
}
__device__ __forceinline__ float ex2(float x) {
    float y;
    asm("ex2.approx.ftz.f32 %0, %1;" : "=f"(y) : "f"(x));
    return y;
}
__device__ __forceinline__ int ld_nc_i32(const int* p) {
    int v;
    asm volatile("ld.global.nc.s32 %0, [%1];" : "=r"(v) : "l"(p));
    return v;
}
__device__ __forceinline__ uint32_t nz(float f) {
    const uint32_t u = __float_as_uint(f);
    return u == 0u ? 0x80000000u : u;
}
__device__ __forceinline__ void st4(uint4* p, uint32_t a, uint32_t b, uint32_t c, uint32_t d) {
    asm volatile("st.relaxed.gpu.global.v4.u32 [%0], {%1,%2,%3,%4};" ::"l"(p), "r"(a), "r"(b), "r"(c), "r"(d) : "memory");
}
__device__ __forceinline__ void st4v(void* p, uint32_t a, uint32_t b, uint32_t c, uint32_t d) {
    asm volatile("st.relaxed.gpu.global.v4.u32 [%0], {%1,%2,%3,%4};" ::"l"(p), "r"(a), "r"(b), "r"(c), "r"(d) : "memory");
}
__device__ __forceinline__ uint32_t nzu(uint32_t u) { return u == 0u ? 0x80000000u : u; }
__device__ __forceinline__ void st4_pred(uint4* p, uint32_t a, uint32_t b, uint32_t c, uint32_t d, int pred) {
    asm volatile("{\n.reg .pred p;\nsetp.ne.s32 p, %5, 0;\n@p st.relaxed.gpu.global.v4.u32 [%0], {%1,%2,%3,%4};\n}"
                 ::"l"(p), "r"(a), "r"(b), "r"(c), "r"(d), "r"(pred) : "memory");
}
__device__ __forceinline__ void st2_pred(uint2* p, uint32_t a, uint32_t b, int pred) {
    asm volatile("{\n.reg .pred p;\nsetp.ne.s32 p, %3, 0;\n@p st.relaxed.gpu.global.v2.u32 [%0], {%1,%2};\n}"
                 ::"l"(p), "r"(a), "r"(b), "r"(pred) : "memory");
}
__device__ __forceinline__ void ld4_pred(uint4& v, const uint4* p, int pred) {
    asm volatile("{\n.reg .pred p;\nsetp.ne.s32 p, %5, 0;\n@p ld.relaxed.gpu.global.v4.u32 {%0,%1,%2,%3}, [%4];\n}"
                 : "+r"(v.x), "+r"(v.y), "+r"(v.z), "+r"(v.w) : "l"(p), "r"(pred) : "memory");
}
__device__ __forceinline__ void ld2_pred(uint2& v, const uint2* p, int pred) {
    asm volatile("{\n.reg .pred p;\nsetp.ne.s32 p, %3, 0;\n@p ld.relaxed.gpu.global.v2.u32 {%0,%1}, [%2];\n}"
                 : "+r"(v.x), "+r"(v.y) : "l"(p), "r"(pred) : "memory");
}
__device__ __forceinline__ void named_bar(int id, int n) {
    asm volatile("bar.sync %0, %1;" ::"r"(id), "r"(n) : "memory");
}

__global__ void __launch_bounds__(NTHREADS, 1)
decode_kernel(const __nv_bfloat16* __restrict__ q, const uint8_t* __restrict__ kc, const uint8_t* __restrict__ vc,
              const int* __restrict__ bt, const int* __restrict__ ctx_ptr, __nv_bfloat16* __restrict__ out,
              int nb, int npass, int use_tmap,
              const __grid_constant__ CUtensorMap tmk, const __grid_constant__ CUtensorMap tmv)
{
    extern __shared__ __align__(1024) uint8_t smem[];
    __shared__ __align__(8) uint64_t s_full[NSLOT], s_empty[NSLOT], s_done, s_clr;
    __shared__ int s_chunk[NCH];
    __shared__ unsigned int s_epoch;
    __shared__ __align__(16) float s_red[NHELP][32];
    __shared__ float2 s_ml[NHELP];

    const int tid = threadIdx.x, lane = tid & 31;
    const int warp = __shfl_sync(0xffffffffu, tid >> 5, 0);
    const int G = gridDim.x, cta = blockIdx.x;
    const int Lk = nb * BS;
    const uint32_t smem_base = smem_u32(smem);

    if (tid == 0) TS(0);
    int ctx = ld_nc_i32(ctx_ptr);
    const int ch0 = (warp >> 1) * G + cta;
    const bool fill = warp < NSLOT - 2;
    int page0 = 0;
    if (lane == 0 && fill && (ch0 >> 2) < nb) page0 = ld_nc_i32(bt + (ch0 >> 2));
    if (lane == 0) {
        if (warp < NSLOT) {
            const int s = warp;
            const int ch = ch0;
            const int page = page0;
            if (use_tmap) asm volatile("prefetch.tensormap [%0];" ::"l"((s & 1) ? &tmv : &tmk) : "memory");
            const uint32_t fb = smem_u32(&s_full[s]);
            mbar_init(fb, 1);
            mbar_init(smem_u32(&s_empty[s]), NCONS);
            asm volatile("fence.mbarrier_init.release.cluster;" ::: "memory");
            const int cx = min(max(ctx, 0), Lk);
            if (fill) {
                if (ch * CH_TOK < cx) {
                    mbar_expect_tx(fb, CH_BYTES);
                    load_chunk(use_tmap, smem_base + s * CH_BYTES, (s & 1) ? &tmv : &tmk, (s & 1) ? vc : kc, page, ch, fb, policy_evict_first());
                    if (!(s & 1)) s_chunk[s >> 1] = ch;
                } else if (!(s & 1)) {
                    s_chunk[s >> 1] = -1;
                    mbar_arrive(fb);
                }
            }
            if (s == 0) TS(1);
        }
        if (warp == NWARPS - 1) {
            mbar_init(smem_u32(&s_done), NCONS);
            mbar_init(smem_u32(&s_clr), NHELP);
#pragma unroll
            for (int s = NWARPS; s < NSLOT; s++) { mbar_init(smem_u32(&s_full[s]), 1); mbar_init(smem_u32(&s_empty[s]), NCONS); }
            asm volatile("fence.mbarrier_init.release.cluster;" ::: "memory");
        }
    }
    unsigned int nxt = 0;
    unsigned int* cnt = nullptr;
    if (tid == NCONS * 32) {
        unsigned int epoch;
        asm volatile("ld.relaxed.gpu.global.u32 %0, [%1];" : "=r"(epoch) : "l"(&g_epoch) : "memory");
        s_epoch = epoch;
        cnt = g_cnt[epoch & 1];
        nxt = atomicAdd(cnt, 1u);
        if (cta == 0) { unsigned int* o = g_cnt[(epoch & 1) ^ 1]; o[0] = 0; o[32] = 0; o[64] = 0; }
    }
    ctx = min(max(ctx, 0), Lk);
    const int nchunks = (ctx + CH_TOK - 1) / CH_TOK;
    __syncwarp();
    asm volatile("bar.arrive %0, %1;" ::"r"(warp < NCONS ? 0 : 3), "r"(NTHREADS) : "memory");

    if (warp == NCONS) {
        named_bar(0, NTHREADS);
        if (lane == 0) {
            {
                int j = NCH - 1;
                uint32_t ph = 1;
                const uint64_t pol = policy_evict_first();
                int ch = (NCH - 1) * G + cta;
                TS(13);
                while (true) {
                    const uint32_t fK = smem_u32(&s_full[2 * j]), fV = fK + 8;
                    const uint32_t eK = smem_u32(&s_empty[2 * j]), eV = eK + 8;
                    if (ch >= nchunks) {
                        mbar_wait(eK, ph);
                        s_chunk[j] = -1;
                        mbar_arrive(fK);
                        break;
                    }
                    int page = ld_nc_i32(bt + (ch >> 2));
                    page = __shfl_sync(1u, page, 0);
                    const uint32_t dst = smem_base + (2 * j) * CH_BYTES;
                    PROD_WAIT(eK, ph);
                    s_chunk[j] = ch;
                    mbar_expect_tx(fK, CH_BYTES);
                    load_chunk(use_tmap, dst, &tmk, kc, page, ch, fK, pol);
                    PROD_WAIT(eV, ph);
                    mbar_expect_tx(fV, CH_BYTES);
                    load_chunk(use_tmap, dst + CH_BYTES, &tmv, vc, page, ch, fV, pol);
                    if (++j == NCH) { j = 0; ph ^= 1; }
                    ch = NCH * G + (int)nxt;
                    if (ch < nchunks) nxt = atomicAdd(cnt, 1u);
                }
            }
            mbar_wait(smem_u32(&s_done), 0);
            TS(8);
            asm volatile("red.relaxed.gpu.global.add.u32 [%0], 1;" ::"l"(cnt + 32) : "memory");
        }
    } else if (warp < NCONS) {
        const int w = warp;
        uint32_t qf[8][2];
        {
            const int n = lane >> 2, h = lane >> 3;
            const uint32_t* qrow = reinterpret_cast<const uint32_t*>(q + (size_t)(8 * w + n) * DH);
#pragma unroll
            for (int j = 0; j < 8; j++) {
                const int d0 = 16 * (j ^ h) + (lane & 3) * 2;
                qf[j][0] = __ldg(qrow + (d0 >> 1));
                qf[j][1] = __ldg(qrow + ((d0 + 8) >> 1));
            }
        }
        uint32_t koff[2], voff[2];
        {
            const int mi = lane >> 3, r = lane & 7, h = r & 3;
            const int tK = (r >> 2) + 2 * (mi & 1), bK = mi >> 1;
            const int tV = (r >> 2) + 2 * (mi >> 1), bV = mi & 1;
            if (use_tmap) {
                koff[0] = ((8 * w + 2 * h) * 4 + tK) * 128 + (((2 * h + bK) ^ tK) << 4);
                voff[0] = ((8 * w + 2 * h) * 4 + tV) * 128 + (((2 * h + bV) ^ tV) << 4);
                koff[1] = (koff[0] + 512) ^ 64;
                voff[1] = (voff[0] + 512) ^ 64;
            } else {
                koff[0] = tK * TOK_BYTES + (4 * w + h) * 256 + ((2 * h + bK) << 4);
                voff[0] = tV * TOK_BYTES + (4 * w + h) * 256 + ((2 * h + bV) << 4);
                koff[1] = koff[0] ^ 128;
                voff[1] = voff[0] ^ 128;
            }
            voff[0] += CH_BYTES; voff[1] += CH_BYTES;
        }
        const bool valid_lane = (((lane >> 2) & 3) == (lane & 3));
        const int tokA = lane >> 4;
        const int src0 = 5 * (lane & 3), src1 = src0 + 16;

        float acc[8][4];
#pragma unroll
        for (int i = 0; i < 8; i++) { acc[i][0] = acc[i][1] = acc[i][2] = acc[i][3] = 0.f; }
        float m0 = NEG_INIT, m1 = NEG_INIT, l0 = 0.f, l1 = 0.f;

#pragma unroll 1
        for (int pass = 0; pass < npass; pass++) {
            {
                int j = 0;
                uint32_t ph = 0;
                while (true) {
                    const uint32_t fK = smem_u32(&s_full[2 * j]), eK = smem_u32(&s_empty[2 * j]);
                    int chunk = 0;
                    if (pass) {
                        CONS_WAIT(fK, ph);
                        chunk = *(volatile int*)&s_chunk[j];
                    }
                    if (chunk < 0) break;
                    const uint32_t sb = smem_base + (2 * j) * CH_BYTES;
                    float c0[4] = {0.f, 0.f, 0.f, 0.f}, c1[4] = {0.f, 0.f, 0.f, 0.f};
                    {
                        uint32_t a[8][4];
#pragma unroll
                        for (int jj = 0; jj < 8; jj++) ldsm4(a[jj], (sb + koff[jj >> 2]) ^ ((jj & 3) << 5));
                        __syncwarp();
                        if (pass && lane == 0) mbar_arrive(eK);
#pragma unroll
                        for (int jj = 0; jj < 8; jj += 2) {
                            mma16816(c0, a[jj], qf[jj][0], qf[jj][1]);
                            mma16816(c1, a[jj + 1], qf[jj + 1][0], qf[jj + 1][1]);
                        }
                    }
                    uint32_t av[8][4];
                    if (pass) CONS_WAIT(fK + 8, ph);
                    {
#pragma unroll
                        for (int i = 0; i < 8; i++) ldsm4t(av[i], (sb + voff[i >> 2]) ^ ((i & 3) << 5));
                        __syncwarp();
                        if (pass && lane == 0) mbar_arrive(eK + 8);
                    }
                    const int rem = ctx - chunk * CH_TOK;
                    const bool vA = valid_lane && (tokA < rem), vB = valid_lane && (tokA + 2 < rem);
                    const float NINF = __int_as_float(0xff800000);
                    const float s0 = vA ? (c0[0] + c1[0]) * QK_SCALE : NINF;
                    const float s1 = vA ? (c0[1] + c1[1]) * QK_SCALE : NINF;
                    const float s2 = vB ? (c0[2] + c1[2]) * QK_SCALE : NINF;
                    const float s3 = vB ? (c0[3] + c1[3]) * QK_SCALE : NINF;
                    const float x0 = fmaxf(s0, s2), x1 = fmaxf(s1, s3);
                    const float y0 = fmaxf(__shfl_sync(0xffffffffu, x0, src0), __shfl_sync(0xffffffffu, x0, src1));
                    const float y1 = fmaxf(__shfl_sync(0xffffffffu, x1, src0), __shfl_sync(0xffffffffu, x1, src1));
                    const float n0 = fmaxf(m0, y0), n1 = fmaxf(m1, y1);
                    if (__any_sync(0xffffffffu, (n0 > m0) || (n1 > m1))) {
                        const float a0 = ex2(m0 - n0), a1 = ex2(m1 - n1);
                        l0 *= a0; l1 *= a1;
#pragma unroll
                        for (int i = 0; i < 8; i++) {
                            acc[i][0] *= a0; acc[i][1] *= a1; acc[i][2] *= a0; acc[i][3] *= a1;
                        }
                        m0 = n0; m1 = n1;
                    }
                    const float p0 = ex2(s0 - m0), p1 = ex2(s1 - m1), p2 = ex2(s2 - m0), p3 = ex2(s3 - m1);
                    l0 += p0 + p2; l1 += p1 + p3;
                    const uint32_t pb0 = movm(pack_bf16(p0, p1));
                    const uint32_t pb1 = movm(pack_bf16(p2, p3));
#pragma unroll
                    for (int i = 0; i < 8; i++) mma16816(acc[i], av[i], pb0, pb1);
                    if (!pass) break;
                    if (++j == NCH) { j = 0; ph ^= 1; }
                }
                if (tid == 0 && pass) TS(3);
            }
            const int h = lane & 3, g = lane >> 2;
            const int rec0 = ((8 * w + 2 * h) * 4) * MAXG + cta;
            if (pass) mbar_wait(smem_u32(&s_clr), 0);
            const float r0 = __shfl_sync(0xffffffffu, l0, src0) + __shfl_sync(0xffffffffu, l0, src1);
            const float r1 = __shfl_sync(0xffffffffu, l1, src0) + __shfl_sync(0xffffffffu, l1, src1);
            st4_pred(reinterpret_cast<uint4*>(g_ml + cta * H + 8 * w + 2 * h), nz(m0), nz(r0), nz(m1), nz(r1), pass && lane < 4);
#pragma unroll
            for (int i0 = 0; i0 < 8; i0 += 2) {
                const int qd = (i0 >> 1) ^ (h >> 1);
                uint2* p = g_rec + (size_t)(rec0 + qd * MAXG) * 8 + g;
                st2_pred(p, nzu(pack_bf16(acc[i0][0], acc[i0][2])), nzu(pack_bf16(acc[i0 + 1][0], acc[i0 + 1][2])), pass);
                st2_pred(p + (size_t)4 * MAXG * 8, nzu(pack_bf16(acc[i0][1], acc[i0][3])), nzu(pack_bf16(acc[i0 + 1][1], acc[i0 + 1][3])), pass);
            }
            __syncwarp();
            if (pass && lane == 0) mbar_arrive(smem_u32(&s_done));
            if (!pass) {
#pragma unroll
                for (int i = 0; i < 8; i++) { acc[i][0] = acc[i][1] = acc[i][2] = acc[i][3] = 0.f; }
                m0 = NEG_INIT; m1 = NEG_INIT; l0 = 0.f; l1 = 0.f;
                if (tid == 0) TS(11);
                named_bar(3, NTHREADS);
                if (tid == 0) TS(12);
            }
        }
        if (tid == 0) TS(4);
    } else {
        const int hw = warp - NCONS - 1;
        const int t = tid - (NCONS + 1) * 32;
        const int grp = t >> 3, x = t & 7;
        named_bar(0, NTHREADS);
        const unsigned int epoch = s_epoch;
        unsigned int* cnt = g_cnt[epoch & 1];
        for (int i = t; i < H * 4 * 4; i += NHELP * 32)
            st4v(g_rec + ((size_t)(i >> 2) * MAXG + cta) * 8 + (i & 3) * 2, 0u, 0u, 0u, 0u);
        if (t < 16) st4v(g_ml + cta * H + 2 * t, 0u, 0u, 0u, 0u);
        __syncwarp();
        if (lane == 0) {
            asm volatile("red.release.gpu.global.add.u32 [%0], 1;" ::"l"(cnt + 64) : "memory");
            asm volatile("fence.acq_rel.gpu;" ::: "memory");
            mbar_arrive(smem_u32(&s_clr));
        }
#pragma unroll 1
        for (int pass = 0; pass < npass; pass++) {
            if (pass && t == 0 && cta < H * 4) {
                uint32_t n = 0;
                while (true) {
                    unsigned int u;
                    asm volatile("ld.acquire.gpu.global.u32 %0, [%1];" : "=r"(u) : "l"(cnt + 64) : "memory");
                    if (u >= (unsigned)(NHELP * G)) break;
                    if (++n > (1u << 24)) __trap();
                    __nanosleep(500);
                }
                if (cta == 0) g_epoch = epoch + 1;
                const unsigned int target = (G > GATE_K) ? (unsigned)(G - GATE_K) : 0u;
                n = 0;
                while (true) {
                    unsigned int v;
                    asm volatile("ld.relaxed.gpu.global.u32 %0, [%1];" : "=r"(v) : "l"(cnt + 32) : "memory");
                    if (v >= target) break;
                    if (++n > (1u << 24)) __trap();
                    __nanosleep(v == 0 ? GATE_SLEEP0 : 0);
                }
                TS(5);
            }
            named_bar(1, NHELP * 32);
            if (cta >= H * 4) continue;

            const uint2* rp = g_rec + (size_t)cta * MAXG * 8 + x;
            uint2 v[NPASS];
            const uint2* mp = g_ml + (cta >> 2);
            uint2 ml[NPASS];
            uint32_t pend = 0;
#pragma unroll
            for (int p = 0; p < NPASS; p++) {
                v[p] = make_uint2(0x80000000u, 0x80000000u);
                ml[p] = make_uint2(__float_as_uint(NEG_INIT), 0x80000000u);
                if (pass && grp + p * NGRP < G) pend |= 1u << p;
            }
            uint32_t n = 0;
            do {
#pragma unroll
                for (int p = 0; p < NPASS; p++) {
                    const int c = grp + p * NGRP;
                    ld2_pred(v[p], rp + c * 8, pend & (1u << p));
                    ld2_pred(ml[p], mp + c * H, pend & (1u << p));
                }
#pragma unroll
                for (int p = 0; p < NPASS; p++) {
                    const bool ok = v[p].x && v[p].y && ml[p].x && ml[p].y;
                    if (ok) pend &= ~(1u << p);
                }
                if (++n > (1u << 22)) __trap();
            } while (pend);
            __syncwarp();
            float Mw = NEG_INIT;
#pragma unroll
            for (int p = 0; p < NPASS; p++) Mw = fmaxf(Mw, __uint_as_float(ml[p].x));
            Mw = fmaxf(Mw, __shfl_xor_sync(0xffffffffu, Mw, 8));
            Mw = fmaxf(Mw, __shfl_xor_sync(0xffffffffu, Mw, 16));
            float a0 = 0.f, a1 = 0.f, a2 = 0.f, a3 = 0.f, al = 0.f;
#pragma unroll
            for (int p = 0; p < NPASS; p++) {
                const float wgt = ex2(__uint_as_float(ml[p].x) - Mw);
                a0 += wgt * __uint_as_float(v[p].x << 16); a1 += wgt * __uint_as_float(v[p].x & 0xffff0000u);
                a2 += wgt * __uint_as_float(v[p].y << 16); a3 += wgt * __uint_as_float(v[p].y & 0xffff0000u);
                al += wgt * __uint_as_float(ml[p].y);
            }
#pragma unroll
            for (int o = 8; o < 32; o <<= 1) {
                a0 += __shfl_xor_sync(0xffffffffu, a0, o);
                a1 += __shfl_xor_sync(0xffffffffu, a1, o);
                a2 += __shfl_xor_sync(0xffffffffu, a2, o);
                a3 += __shfl_xor_sync(0xffffffffu, a3, o);
                al += __shfl_xor_sync(0xffffffffu, al, o);
            }
            if (lane < 8) *reinterpret_cast<float4*>(&s_red[hw][lane * 4]) = make_float4(a0, a1, a2, a3);
            if (lane == 0) s_ml[hw] = make_float2(Mw, al);
            named_bar(1, NHELP * 32);
            if (hw == 0) {
                float M = NEG_INIT;
                float2 wml[NHELP];
#pragma unroll
                for (int k = 0; k < NHELP; k++) { wml[k] = s_ml[k]; M = fmaxf(M, wml[k].x); }
                float r = 0.f, L = 0.f;
#pragma unroll
                for (int k = 0; k < NHELP; k++) {
                    const float wgt = ex2(wml[k].x - M);
                    r += wgt * s_red[k][lane];
                    L += wgt * wml[k].y;
                }
                const int head = cta >> 2, qd = cta & 3, h = (head >> 1) & 3;
                const int d = qd * 32 + 16 * (((lane >> 1) & 1) ^ (h & 1)) + 8 * (lane & 1) + (lane >> 2);
                if (pass && M < MASKED + 150.f) {
                    const float Mall = fmaxf(M, MASKED);
                    const float wa = ex2(M - Mall), wb = ex2(MASKED - Mall);
                    float sv = 0.f;
                    for (int tk = ctx; tk < Lk; tk++) {
                        const int pg = bt[tk >> 4];
                        const __nv_bfloat16* vp = reinterpret_cast<const __nv_bfloat16*>(
                            vc + ((size_t)pg * BS + (tk & 15)) * TOK_BYTES) + (head >> 1) * DH + d;
                        sv += __bfloat162float(*vp);
                    }
                    r = wa * r + wb * sv;
                    L = wa * L + wb * (float)(Lk - ctx);
                }
                const __nv_bfloat16 o = __float2bfloat16(__fdividef(r, L));
                if (pass) out[head * DH + d] = o;
                if (pass && t == 0) TS(6);
            }
        }
    }
}

}

extern "C" void kernel_launch(void* const* d_in, const int* in_sizes, int n_in, void* d_out, int out_size) {
    (void)n_in; (void)out_size;
    const __nv_bfloat16* q = (const __nv_bfloat16*)d_in[0];
    const uint8_t* kc = (const uint8_t*)d_in[1];
    const uint8_t* vc = (const uint8_t*)d_in[2];
    const int* bt = (const int*)d_in[3];
    const int* ctx = (const int*)d_in[4];
    __nv_bfloat16* out = (__nv_bfloat16*)d_out;
    const int B = in_sizes[4];
    const int nb = in_sizes[3] / B;

    typedef CUresult (*EncodeFn)(CUtensorMap*, CUtensorMapDataType, cuuint32_t, void*, const cuuint64_t*, const cuuint64_t*,
                                 const cuuint32_t*, const cuuint32_t*, CUtensorMapInterleave, CUtensorMapSwizzle,
                                 CUtensorMapL2promotion, CUtensorMapFloatOOBfill);
    static int grid = 0;
    static EncodeFn encode = nullptr;
    if (grid == 0) {
        int dev = 0, sms = 0;
        cudaGetDevice(&dev);
        cudaDeviceGetAttribute(&sms, cudaDevAttrMultiProcessorCount, dev);
        cudaFuncSetAttribute(decode_kernel, cudaFuncAttributeMaxDynamicSharedMemorySize, MAX_SMEM);
        grid = sms < MAXG ? sms : MAXG;
        if (grid < H * 4) grid = H * 4;
        void* fn = nullptr;
        cudaDriverEntryPointQueryResult qr;
        if (cudaGetDriverEntryPoint("cuTensorMapEncodeTiled", &fn, cudaEnableDefault, &qr) == cudaSuccess &&
            qr == cudaDriverEntryPointSuccess)
            encode = (EncodeFn)fn;
        (void)cudaGetLastError();
    }
    CUtensorMap tmk, tmv;
    memset(&tmk, 0, sizeof(tmk)); memset(&tmv, 0, sizeof(tmv));
    int use_tmap = 0;
    if (encode) {
        const cuuint64_t n_phys = (cuuint64_t)in_sizes[1] / (BS * HKV * DH);
        const cuuint64_t dims[4] = {64, (cuuint64_t)BS, (cuuint64_t)(HKV * 2), n_phys};
        const cuuint64_t strides[3] = {(cuuint64_t)TOK_BYTES, 128, (cuuint64_t)BS * TOK_BYTES};
        const cuuint32_t box[4] = {64, (cuuint32_t)CH_TOK, (cuuint32_t)(HKV * 2), 1};
        const cuuint32_t es[4] = {1, 1, 1, 1};
        const CUresult r1 = encode(&tmk, CU_TENSOR_MAP_DATA_TYPE_BFLOAT16, 4, (void*)kc, dims, strides, box, es,
                                   CU_TENSOR_MAP_INTERLEAVE_NONE, CU_TENSOR_MAP_SWIZZLE_128B,
                                   CU_TENSOR_MAP_L2_PROMOTION_NONE, CU_TENSOR_MAP_FLOAT_OOB_FILL_NONE);
        const CUresult r2 = encode(&tmv, CU_TENSOR_MAP_DATA_TYPE_BFLOAT16, 4, (void*)vc, dims, strides, box, es,
                                   CU_TENSOR_MAP_INTERLEAVE_NONE, CU_TENSOR_MAP_SWIZZLE_128B,
                                   CU_TENSOR_MAP_L2_PROMOTION_NONE, CU_TENSOR_MAP_FLOAT_OOB_FILL_NONE);
        use_tmap = (r1 == CUDA_SUCCESS && r2 == CUDA_SUCCESS) ? 1 : 0;
    }
    for (int b = 0; b < B; b++) {
        decode_kernel<<<grid, NTHREADS, MAX_SMEM, cudaStreamPerThread>>>(
            q + (size_t)b * H * DH, kc, vc, bt + (size_t)b * nb, ctx + b, out + (size_t)b * H * DH, nb, 2, use_tmap, tmk, tmv);
    }
}
```

```cpp
#include <cuda_runtime.h>
#include <cuda.h>
#include <cuda_bf16.h>
#include <stdint.h>
#include <string.h>

namespace {

constexpr int H = 32, HKV = 16, DH = 128, BS = 16;
constexpr int TOK_BYTES = HKV * DH * 2;
constexpr int CH_TOK = 4;
constexpr int CH_BYTES = CH_TOK * TOK_BYTES;
constexpr int NCH = 7;
constexpr int GATE_K = 96;
constexpr int NSLOT = 2 * NCH;
constexpr int NCONS = 4;
constexpr int NHELP = 8;
constexpr int NWARPS = NCONS + 1 + NHELP;
constexpr int NTHREADS = NWARPS * 32;
constexpr int MAXG = 160;
constexpr int NGRP = NHELP * 4;
constexpr int NPASS = MAXG / NGRP;
constexpr int SMEM_RING = NSLOT * CH_BYTES;
constexpr int MIN_SMEM = 120 * 1024;
constexpr int MAX_SMEM = (SMEM_RING > MIN_SMEM) ? SMEM_RING : MIN_SMEM;
static_assert(NSLOT - 2 <= NWARPS, "prologue issue uses one warp per slot");

constexpr float NEG_INIT = -1.0e30f;
constexpr float LOG2E = 1.4426950408889634f;
constexpr float QK_SCALE = 0.08838834764831845f * LOG2E;
constexpr float MASKED = -998244352.0f * LOG2E;

__device__ uint2 g_rec[H * 4 * MAXG * 8];
__device__ uint2 g_ml[MAXG * H];
__device__ unsigned int g_epoch;
__device__ unsigned int g_cnt[2][3 * 32];

__device__ __forceinline__ uint32_t smem_u32(const void* p) { return (uint32_t)__cvta_generic_to_shared(p); }
__device__ __forceinline__ void mbar_init(uint32_t bar, int cnt) {
    asm volatile("mbarrier.init.shared::cta.b64 [%0], %1;" ::"r"(bar), "r"(cnt) : "memory");
}
__device__ __forceinline__ void mbar_expect_tx(uint32_t bar, uint32_t bytes) {
    asm volatile("mbarrier.arrive.expect_tx.shared::cta.b64 _, [%0], %1;" ::"r"(bar), "r"(bytes) : "memory");
}
__device__ __forceinline__ void mbar_arrive(uint32_t bar) {
    asm volatile("mbarrier.arrive.shared::cta.b64 _, [%0];" ::"r"(bar) : "memory");
}
__device__ __forceinline__ bool mbar_try(uint32_t bar, uint32_t parity) {
    uint32_t ok;
    asm volatile(
        "{\n.reg .pred p;\n"
        "mbarrier.try_wait.parity.shared::cta.b64 p, [%1], %2;\n"
        "selp.u32 %0, 1, 0, p;\n}"
        : "=r"(ok) : "r"(bar), "r"(parity) : "memory");
    return ok != 0;
}
__device__ __forceinline__ void mbar_wait(uint32_t bar, uint32_t parity) {
    if (mbar_try(bar, parity)) return;
    uint32_t n = 0;
    while (!mbar_try(bar, parity)) {
        if (++n > (1u << 24)) __trap();
    }
}
__device__ __forceinline__ void bulk_g2s_ef(uint32_t dst, const void* src, uint32_t bytes, uint32_t bar, uint64_t pol) {
    asm volatile("cp.async.bulk.shared::cluster.global.mbarrier::complete_tx::bytes.L2::cache_hint [%0], [%1], %2, [%3], %4;"
                 ::"r"(dst), "l"(src), "r"(bytes), "r"(bar), "l"(pol) : "memory");
}
template <bool TMAP>
__device__ __forceinline__ void load_chunk(uint32_t dst, const CUtensorMap* tm, const uint8_t* base,
                                           int page, int ch, uint32_t bar, uint64_t pol) {
    if (TMAP) {
        asm volatile("cp.async.bulk.tensor.4d.shared::cluster.global.mbarrier::complete_tx::bytes.L2::cache_hint "
                     "[%0], [%1, {%3, %4, %5, %6}], [%2], %7;"
                     ::"r"(dst), "l"(tm), "r"(bar), "r"(0), "r"((ch & 3) * CH_TOK), "r"(0), "r"(page), "l"(pol) : "memory");
    } else {
        const size_t off = ((size_t)page * BS + (size_t)((ch & 3) * CH_TOK)) * TOK_BYTES;
        bulk_g2s_ef(dst, base + off, CH_BYTES, bar, pol);
    }
}
__device__ __forceinline__ uint64_t policy_evict_first() {
    uint64_t pol;
    asm volatile("createpolicy.fractional.L2::evict_first.b64 %0, 1.0;" : "=l"(pol));
    return pol;
}
__device__ __forceinline__ void ldsm4(uint32_t (&r)[4], uint32_t addr) {
    asm volatile("ldmatrix.sync.aligned.m8n8.x4.shared.b16 {%0,%1,%2,%3}, [%4];"
                 : "=r"(r[0]), "=r"(r[1]), "=r"(r[2]), "=r"(r[3]) : "r"(addr) : "memory");
}
__device__ __forceinline__ void ldsm4t(uint32_t (&r)[4], uint32_t addr) {
    asm volatile("ldmatrix.sync.aligned.m8n8.x4.trans.shared.b16 {%0,%1,%2,%3}, [%4];"
                 : "=r"(r[0]), "=r"(r[1]), "=r"(r[2]), "=r"(r[3]) : "r"(addr) : "memory");
}
__device__ __forceinline__ void mma16816(float (&c)[4], const uint32_t (&a)[4], uint32_t b0, uint32_t b1) {
    asm volatile("mma.sync.aligned.m16n8k16.row.col.f32.bf16.bf16.f32 {%0,%1,%2,%3}, {%4,%5,%6,%7}, {%8,%9}, {%0,%1,%2,%3};"
                 : "+f"(c[0]), "+f"(c[1]), "+f"(c[2]), "+f"(c[3])
                 : "r"(a[0]), "r"(a[1]), "r"(a[2]), "r"(a[3]), "r"(b0), "r"(b1));
}
__device__ __forceinline__ uint32_t movm(uint32_t a) {
    uint32_t d;
    asm volatile("movmatrix.sync.aligned.m8n8.trans.b16 %0, %1;" : "=r"(d) : "r"(a));
    return d;
}
__device__ __forceinline__ uint32_t pack_bf16(float lo, float hi) {
    uint32_t d;
    asm("cvt.rn.bf16x2.f32 %0, %1, %2;" : "=r"(d) : "f"(hi), "f"(lo));
    return d;
}
__device__ __forceinline__ float ex2(float x) {
    float y;
    asm("ex2.approx.ftz.f32 %0, %1;" : "=f"(y) : "f"(x));
    return y;
}
__device__ __forceinline__ int ld_nc_i32(const int* p) {
    int v;
    asm volatile("ld.global.nc.s32 %0, [%1];" : "=r"(v) : "l"(p));
    return v;
}
__device__ __forceinline__ uint32_t nz(float f) {
    const uint32_t u = __float_as_uint(f);
    return u == 0u ? 0x80000000u : u;
}
__device__ __forceinline__ void st4v(void* p, uint32_t a, uint32_t b, uint32_t c, uint32_t d) {
    asm volatile("st.relaxed.gpu.global.v4.u32 [%0], {%1,%2,%3,%4};" ::"l"(p), "r"(a), "r"(b), "r"(c), "r"(d) : "memory");
}
__device__ __forceinline__ uint32_t nzu(uint32_t u) { return u == 0u ? 0x80000000u : u; }
__device__ __forceinline__ void st4_pred(uint4* p, uint32_t a, uint32_t b, uint32_t c, uint32_t d, int pred) {
    asm volatile("{\n.reg .pred p;\nsetp.ne.s32 p, %5, 0;\n@p st.relaxed.gpu.global.v4.u32 [%0], {%1,%2,%3,%4};\n}"
                 ::"l"(p), "r"(a), "r"(b), "r"(c), "r"(d), "r"(pred) : "memory");
}
__device__ __forceinline__ void st2_pred(uint2* p, uint32_t a, uint32_t b, int pred) {
    asm volatile("{\n.reg .pred p;\nsetp.ne.s32 p, %3, 0;\n@p st.relaxed.gpu.global.v2.u32 [%0], {%1,%2};\n}"
                 ::"l"(p), "r"(a), "r"(b), "r"(pred) : "memory");
}
__device__ __forceinline__ void ld2_pred(uint2& v, const uint2* p, int pred) {
    asm volatile("{\n.reg .pred p;\nsetp.ne.s32 p, %3, 0;\n@p ld.relaxed.gpu.global.v2.u32 {%0,%1}, [%2];\n}"
                 : "+r"(v.x), "+r"(v.y) : "l"(p), "r"(pred) : "memory");
}
__device__ __forceinline__ void named_bar(int id, int n) {
    asm volatile("bar.sync %0, %1;" ::"r"(id), "r"(n) : "memory");
}

template <bool TMAP>
__global__ void __launch_bounds__(NTHREADS, 1)
decode_kernel(const __nv_bfloat16* __restrict__ q, const uint8_t* __restrict__ kc, const uint8_t* __restrict__ vc,
              const int* __restrict__ bt, const int* __restrict__ ctx_ptr, __nv_bfloat16* __restrict__ out,
              int nb, int npass,
              const __grid_constant__ CUtensorMap tmk, const __grid_constant__ CUtensorMap tmv)
{
    extern __shared__ __align__(1024) uint8_t smem[];
    __shared__ __align__(8) uint64_t s_full[NSLOT], s_empty[NSLOT], s_done, s_clr;
    __shared__ int s_chunk[NCH];
    __shared__ unsigned int s_epoch;
    __shared__ __align__(16) float s_red[NHELP][32];
    __shared__ float2 s_ml[NHELP];

    const int tid = threadIdx.x, lane = tid & 31;
    const int warp = __shfl_sync(0xffffffffu, tid >> 5, 0);
    const int G = gridDim.x, cta = blockIdx.x;
    const int Lk = nb * BS;
    const uint32_t smem_base = smem_u32(smem);
    int ctx = ld_nc_i32(ctx_ptr);
    const int ch0 = (warp >> 1) * G + cta;
    const bool fill = warp < NSLOT - 2;
    int page0 = 0;
    if (lane == 0 && fill && (ch0 >> 2) < nb) page0 = ld_nc_i32(bt + (ch0 >> 2));
    if (lane == 0) {
        if (warp < NSLOT) {
            const int s = warp;
            const int ch = ch0;
            const int page = page0;
            if (TMAP) asm volatile("prefetch.tensormap [%0];" ::"l"((s & 1) ? &tmv : &tmk) : "memory");
            const uint32_t fb = smem_u32(&s_full[s]);
            mbar_init(fb, 1);
            mbar_init(smem_u32(&s_empty[s]), NCONS);
            asm volatile("fence.mbarrier_init.release.cluster;" ::: "memory");
            const int cx = min(max(ctx, 0), Lk);
            if (fill) {
                if (ch * CH_TOK < cx) {
                    mbar_expect_tx(fb, CH_BYTES);
                    load_chunk<TMAP>(smem_base + s * CH_BYTES, (s & 1) ? &tmv : &tmk, (s & 1) ? vc : kc, page, ch, fb, policy_evict_first());
                    if (!(s & 1)) s_chunk[s >> 1] = ch;
                } else if (!(s & 1)) {
                    s_chunk[s >> 1] = -1;
                    mbar_arrive(fb);
                }
            }
        }
        if (warp == NWARPS - 1) {
            mbar_init(smem_u32(&s_done), NCONS);
            mbar_init(smem_u32(&s_clr), NHELP);
#pragma unroll
            for (int s = NWARPS; s < NSLOT; s++) { mbar_init(smem_u32(&s_full[s]), 1); mbar_init(smem_u32(&s_empty[s]), NCONS); }
            asm volatile("fence.mbarrier_init.release.cluster;" ::: "memory");
        }
    }
    unsigned int nxt = 0;
    unsigned int* cnt = nullptr;
    if (tid == NCONS * 32) {
        unsigned int epoch;
        asm volatile("ld.relaxed.gpu.global.u32 %0, [%1];" : "=r"(epoch) : "l"(&g_epoch) : "memory");
        s_epoch = epoch;
        cnt = g_cnt[epoch & 1];
        nxt = atomicAdd(cnt, 1u);
        if (cta == 0) { unsigned int* o = g_cnt[(epoch & 1) ^ 1]; o[0] = 0; o[32] = 0; o[64] = 0; }
    }
    ctx = min(max(ctx, 0), Lk);
    const int nchunks = (ctx + CH_TOK - 1) / CH_TOK;
    __syncwarp();
    asm volatile("bar.arrive %0, %1;" ::"r"(warp < NCONS ? 0 : 3), "r"(NTHREADS) : "memory");

    if (warp == NCONS) {
        named_bar(0, NTHREADS);
        if (lane == 0) {
            {
                int j = NCH - 1;
                uint32_t ph = 1;
                const uint64_t pol = policy_evict_first();
                int ch = (NCH - 1) * G + cta;
                while (true) {
                    const uint32_t fK = smem_u32(&s_full[2 * j]), fV = fK + 8;
                    const uint32_t eK = smem_u32(&s_empty[2 * j]), eV = eK + 8;
                    if (ch >= nchunks) {
                        mbar_wait(eK, ph);
                        s_chunk[j] = -1;
                        mbar_arrive(fK);
                        break;
                    }
                    int page = ld_nc_i32(bt + (ch >> 2));
                    page = __shfl_sync(1u, page, 0);
                    const uint32_t dst = smem_base + (2 * j) * CH_BYTES;
                    mbar_wait(eK, ph);
                    s_chunk[j] = ch;
                    mbar_expect_tx(fK, CH_BYTES);
                    load_chunk<TMAP>(dst, &tmk, kc, page, ch, fK, pol);
                    mbar_wait(eV, ph);
                    mbar_expect_tx(fV, CH_BYTES);
                    load_chunk<TMAP>(dst + CH_BYTES, &tmv, vc, page, ch, fV, pol);
                    if (++j == NCH) { j = 0; ph ^= 1; }
                    ch = NCH * G + (int)nxt;
                    if (ch < nchunks) nxt = atomicAdd(cnt, 1u);
                }
            }
            mbar_wait(smem_u32(&s_done), 0);
            asm volatile("red.relaxed.gpu.global.add.u32 [%0], 1;" ::"l"(cnt + 32) : "memory");
        }
    } else if (warp < NCONS) {
        const int w = warp;
        uint32_t qf[8][2];
        {
            const int n = lane >> 2, h = lane >> 3;
            const uint32_t* qrow = reinterpret_cast<const uint32_t*>(q + (size_t)(8 * w + n) * DH);
#pragma unroll
            for (int j = 0; j < 8; j++) {
                const int d0 = 16 * (j ^ h) + (lane & 3) * 2;
                qf[j][0] = __ldg(qrow + (d0 >> 1));
                qf[j][1] = __ldg(qrow + ((d0 + 8) >> 1));
            }
        }
        uint32_t koff[2], voff[2];
        {
            const int mi = lane >> 3, r = lane & 7, h = r & 3;
            const int tK = (r >> 2) + 2 * (mi & 1), bK = mi >> 1;
            const int tV = (r >> 2) + 2 * (mi >> 1), bV = mi & 1;
            if (TMAP) {
                koff[0] = ((8 * w + 2 * h) * 4 + tK) * 128 + (((2 * h + bK) ^ tK) << 4);
                voff[0] = ((8 * w + 2 * h) * 4 + tV) * 128 + (((2 * h + bV) ^ tV) << 4);
                koff[1] = (koff[0] + 512) ^ 64;
                voff[1] = (voff[0] + 512) ^ 64;
            } else {
                koff[0] = tK * TOK_BYTES + (4 * w + h) * 256 + ((2 * h + bK) << 4);
                voff[0] = tV * TOK_BYTES + (4 * w + h) * 256 + ((2 * h + bV) << 4);
                koff[1] = koff[0] ^ 128;
                voff[1] = voff[0] ^ 128;
            }
            voff[0] += CH_BYTES; voff[1] += CH_BYTES;
        }
        const bool valid_lane = (((lane >> 2) & 3) == (lane & 3));
        const int tokA = lane >> 4;
        const int src0 = 5 * (lane & 3), src1 = src0 + 16;

        float acc[8][4];
#pragma unroll
        for (int i = 0; i < 8; i++) { acc[i][0] = acc[i][1] = acc[i][2] = acc[i][3] = 0.f; }
        float m0 = NEG_INIT, m1 = NEG_INIT, l0 = 0.f, l1 = 0.f;

#pragma unroll 1
        for (int pass = 0; pass < npass; pass++) {
            {
                int j = 0;
                uint32_t ph = 0;
                while (true) {
                    const uint32_t fK = smem_u32(&s_full[2 * j]), eK = smem_u32(&s_empty[2 * j]);
                    int chunk = 0;
                    if (pass) {
                        mbar_wait(fK, ph);
                        chunk = *(volatile int*)&s_chunk[j];
                    }
                    if (chunk < 0) break;
                    const uint32_t sb = smem_base + (2 * j) * CH_BYTES;
                    float c0[4] = {0.f, 0.f, 0.f, 0.f}, c1[4] = {0.f, 0.f, 0.f, 0.f};
                    {
                        uint32_t a[8][4];
#pragma unroll
                        for (int jj = 0; jj < 8; jj++) ldsm4(a[jj], (sb + koff[jj >> 2]) ^ ((jj & 3) << 5));
                        __syncwarp();
                        if (pass && lane == 0) mbar_arrive(eK);
#pragma unroll
                        for (int jj = 0; jj < 8; jj += 2) {
                            mma16816(c0, a[jj], qf[jj][0], qf[jj][1]);
                            mma16816(c1, a[jj + 1], qf[jj + 1][0], qf[jj + 1][1]);
                        }
                    }
                    uint32_t av[8][4];
                    if (pass) mbar_wait(fK + 8, ph);
                    {
#pragma unroll
                        for (int i = 0; i < 8; i++) ldsm4t(av[i], (sb + voff[i >> 2]) ^ ((i & 3) << 5));
                        __syncwarp();
                        if (pass && lane == 0) mbar_arrive(eK + 8);
                    }
                    const int rem = ctx - chunk * CH_TOK;
                    const bool vA = valid_lane && (tokA < rem), vB = valid_lane && (tokA + 2 < rem);
                    const float NINF = __int_as_float(0xff800000);
                    const float s0 = vA ? (c0[0] + c1[0]) * QK_SCALE : NINF;
                    const float s1 = vA ? (c0[1] + c1[1]) * QK_SCALE : NINF;
                    const float s2 = vB ? (c0[2] + c1[2]) * QK_SCALE : NINF;
                    const float s3 = vB ? (c0[3] + c1[3]) * QK_SCALE : NINF;
                    const float x0 = fmaxf(s0, s2), x1 = fmaxf(s1, s3);
                    const float y0 = fmaxf(__shfl_sync(0xffffffffu, x0, src0), __shfl_sync(0xffffffffu, x0, src1));
                    const float y1 = fmaxf(__shfl_sync(0xffffffffu, x1, src0), __shfl_sync(0xffffffffu, x1, src1));
                    const float n0 = fmaxf(m0, y0), n1 = fmaxf(m1, y1);
                    if (__any_sync(0xffffffffu, (n0 > m0) || (n1 > m1))) {
                        const float a0 = ex2(m0 - n0), a1 = ex2(m1 - n1);
                        l0 *= a0; l1 *= a1;
#pragma unroll
                        for (int i = 0; i < 8; i++) {
                            acc[i][0] *= a0; acc[i][1] *= a1; acc[i][2] *= a0; acc[i][3] *= a1;
                        }
                        m0 = n0; m1 = n1;
                    }
                    const float p0 = ex2(s0 - m0), p1 = ex2(s1 - m1), p2 = ex2(s2 - m0), p3 = ex2(s3 - m1);
                    l0 += p0 + p2; l1 += p1 + p3;
                    const uint32_t pb0 = movm(pack_bf16(p0, p1));
                    const uint32_t pb1 = movm(pack_bf16(p2, p3));
#pragma unroll
                    for (int i = 0; i < 8; i++) mma16816(acc[i], av[i], pb0, pb1);
                    if (!pass) break;
                    if (++j == NCH) { j = 0; ph ^= 1; }
                }
            }
            const int h = lane & 3, g = lane >> 2;
            const int rec0 = ((8 * w + 2 * h) * 4) * MAXG + cta;
            if (pass) mbar_wait(smem_u32(&s_clr), 0);
            const float r0 = __shfl_sync(0xffffffffu, l0, src0) + __shfl_sync(0xffffffffu, l0, src1);
            const float r1 = __shfl_sync(0xffffffffu, l1, src0) + __shfl_sync(0xffffffffu, l1, src1);
            st4_pred(reinterpret_cast<uint4*>(g_ml + cta * H + 8 * w + 2 * h), nz(m0), nz(r0), nz(m1), nz(r1), pass && lane < 4);
#pragma unroll
            for (int i0 = 0; i0 < 8; i0 += 2) {
                const int qd = (i0 >> 1) ^ (h >> 1);
                uint2* p = g_rec + (size_t)(rec0 + qd * MAXG) * 8 + g;
                st2_pred(p, nzu(pack_bf16(acc[i0][0], acc[i0][2])), nzu(pack_bf16(acc[i0 + 1][0], acc[i0 + 1][2])), pass);
                st2_pred(p + (size_t)4 * MAXG * 8, nzu(pack_bf16(acc[i0][1], acc[i0][3])), nzu(pack_bf16(acc[i0 + 1][1], acc[i0 + 1][3])), pass);
            }
            __syncwarp();
            if (pass && lane == 0) mbar_arrive(smem_u32(&s_done));
            if (!pass) {
#pragma unroll
                for (int i = 0; i < 8; i++) { acc[i][0] = acc[i][1] = acc[i][2] = acc[i][3] = 0.f; }
                m0 = NEG_INIT; m1 = NEG_INIT; l0 = 0.f; l1 = 0.f;
                named_bar(3, NTHREADS);
            }
        }
    } else {
        const int hw = warp - NCONS - 1;
        const int t = tid - (NCONS + 1) * 32;
        const int grp = t >> 3, x = t & 7;
        named_bar(0, NTHREADS);
        const unsigned int epoch = s_epoch;
        unsigned int* cnt = g_cnt[epoch & 1];
        for (int i = t; i < H * 4 * 4; i += NHELP * 32)
            st4v(g_rec + ((size_t)(i >> 2) * MAXG + cta) * 8 + (i & 3) * 2, 0u, 0u, 0u, 0u);
        if (t < 16) st4v(g_ml + cta * H + 2 * t, 0u, 0u, 0u, 0u);
        __syncwarp();
        if (lane == 0) {
            asm volatile("red.release.gpu.global.add.u32 [%0], 1;" ::"l"(cnt + 64) : "memory");
            asm volatile("fence.acq_rel.gpu;" ::: "memory");
            mbar_arrive(smem_u32(&s_clr));
        }
#pragma unroll 1
        for (int pass = 0; pass < npass; pass++) {
            if (pass && t == 0 && cta < H * 4) {
                uint32_t n = 0;
                while (true) {
                    unsigned int u;
                    asm volatile("ld.acquire.gpu.global.u32 %0, [%1];" : "=r"(u) : "l"(cnt + 64) : "memory");
                    if (u >= (unsigned)(NHELP * G)) break;
                    if (++n > (1u << 24)) __trap();
                    __nanosleep(500);
                }
                if (cta == 0) g_epoch = epoch + 1;
                const unsigned int target = (G > GATE_K) ? (unsigned)(G - GATE_K) : 0u;
                n = 0;
                while (true) {
                    unsigned int v;
                    asm volatile("ld.relaxed.gpu.global.u32 %0, [%1];" : "=r"(v) : "l"(cnt + 32) : "memory");
                    if (v >= target) break;
                    if (++n > (1u << 24)) __trap();
                    __nanosleep(v == 0 ? 400 : 0);
                }
            }
            named_bar(1, NHELP * 32);
            if (cta >= H * 4) continue;

            const uint2* rp = g_rec + (size_t)cta * MAXG * 8 + x;
            uint2 v[NPASS];
            const uint2* mp = g_ml + (cta >> 2);
            uint2 ml[NPASS];
            uint32_t pend = 0;
#pragma unroll
            for (int p = 0; p < NPASS; p++) {
                v[p] = make_uint2(0x80000000u, 0x80000000u);
                ml[p] = make_uint2(__float_as_uint(NEG_INIT), 0x80000000u);
                if (pass && grp + p * NGRP < G) pend |= 1u << p;
            }
            uint32_t n = 0;
            do {
#pragma unroll
                for (int p = 0; p < NPASS; p++) {
                    const int c = grp + p * NGRP;
                    ld2_pred(v[p], rp + c * 8, pend & (1u << p));
                    ld2_pred(ml[p], mp + c * H, pend & (1u << p));
                }
#pragma unroll
                for (int p = 0; p < NPASS; p++) {
                    const bool ok = v[p].x && v[p].y && ml[p].x && ml[p].y;
                    if (ok) pend &= ~(1u << p);
                }
                if (++n > (1u << 22)) __trap();
            } while (pend);
            __syncwarp();
            float Mw = NEG_INIT;
#pragma unroll
            for (int p = 0; p < NPASS; p++) Mw = fmaxf(Mw, __uint_as_float(ml[p].x));
            Mw = fmaxf(Mw, __shfl_xor_sync(0xffffffffu, Mw, 8));
            Mw = fmaxf(Mw, __shfl_xor_sync(0xffffffffu, Mw, 16));
            float a0 = 0.f, a1 = 0.f, a2 = 0.f, a3 = 0.f, al = 0.f;
#pragma unroll
            for (int p = 0; p < NPASS; p++) {
                const float wgt = ex2(__uint_as_float(ml[p].x) - Mw);
                a0 += wgt * __uint_as_float(v[p].x << 16); a1 += wgt * __uint_as_float(v[p].x & 0xffff0000u);
                a2 += wgt * __uint_as_float(v[p].y << 16); a3 += wgt * __uint_as_float(v[p].y & 0xffff0000u);
                al += wgt * __uint_as_float(ml[p].y);
            }
#pragma unroll
            for (int o = 8; o < 32; o <<= 1) {
                a0 += __shfl_xor_sync(0xffffffffu, a0, o);
                a1 += __shfl_xor_sync(0xffffffffu, a1, o);
                a2 += __shfl_xor_sync(0xffffffffu, a2, o);
                a3 += __shfl_xor_sync(0xffffffffu, a3, o);
                al += __shfl_xor_sync(0xffffffffu, al, o);
            }
            if (lane < 8) *reinterpret_cast<float4*>(&s_red[hw][lane * 4]) = make_float4(a0, a1, a2, a3);
            if (lane == 0) s_ml[hw] = make_float2(Mw, al);
            named_bar(1, NHELP * 32);
            if (hw == 0) {
                float M = NEG_INIT;
                float2 wml[NHELP];
#pragma unroll
                for (int k = 0; k < NHELP; k++) { wml[k] = s_ml[k]; M = fmaxf(M, wml[k].x); }
                float r = 0.f, L = 0.f;
#pragma unroll
                for (int k = 0; k < NHELP; k++) {
                    const float wgt = ex2(wml[k].x - M);
                    r += wgt * s_red[k][lane];
                    L += wgt * wml[k].y;
                }
                const int head = cta >> 2, qd = cta & 3, h = (head >> 1) & 3;
                const int d = qd * 32 + 16 * (((lane >> 1) & 1) ^ (h & 1)) + 8 * (lane & 1) + (lane >> 2);
                if (pass && M < MASKED + 150.f) {
                    const float Mall = fmaxf(M, MASKED);
                    const float wa = ex2(M - Mall), wb = ex2(MASKED - Mall);
                    float sv = 0.f;
                    for (int tk = ctx; tk < Lk; tk++) {
                        const int pg = bt[tk >> 4];
                        const __nv_bfloat16* vp = reinterpret_cast<const __nv_bfloat16*>(
                            vc + ((size_t)pg * BS + (tk & 15)) * TOK_BYTES) + (head >> 1) * DH + d;
                        sv += __bfloat162float(*vp);
                    }
                    r = wa * r + wb * sv;
                    L = wa * L + wb * (float)(Lk - ctx);
                }
                const __nv_bfloat16 o = __float2bfloat16(__fdividef(r, L));
                if (pass) out[head * DH + d] = o;
            }
        }
    }
}

}

extern "C" void kernel_launch(void* const* d_in, const int* in_sizes, int n_in, void* d_out, int out_size) {
    (void)n_in; (void)out_size;
    const __nv_bfloat16* q = (const __nv_bfloat16*)d_in[0];
    const uint8_t* kc = (const uint8_t*)d_in[1];
    const uint8_t* vc = (const uint8_t*)d_in[2];
    const int* bt = (const int*)d_in[3];
    const int* ctx = (const int*)d_in[4];
    __nv_bfloat16* out = (__nv_bfloat16*)d_out;
    const int B = in_sizes[4];
    const int nb = in_sizes[3] / B;

    typedef CUresult (*EncodeFn)(CUtensorMap*, CUtensorMapDataType, cuuint32_t, void*, const cuuint64_t*, const cuuint64_t*,
                                 const cuuint32_t*, const cuuint32_t*, CUtensorMapInterleave, CUtensorMapSwizzle,
                                 CUtensorMapL2promotion, CUtensorMapFloatOOBfill);
    static int grid = 0;
    static EncodeFn encode = nullptr;
    if (grid == 0) {
        int dev = 0, sms = 0;
        cudaGetDevice(&dev);
        cudaDeviceGetAttribute(&sms, cudaDevAttrMultiProcessorCount, dev);
        cudaFuncSetAttribute(decode_kernel<true>, cudaFuncAttributeMaxDynamicSharedMemorySize, MAX_SMEM);
        cudaFuncSetAttribute(decode_kernel<false>, cudaFuncAttributeMaxDynamicSharedMemorySize, MAX_SMEM);
        grid = sms < MAXG ? sms : MAXG;
        if (grid < H * 4) grid = H * 4;
        void* fn = nullptr;
        cudaDriverEntryPointQueryResult qr;
        if (cudaGetDriverEntryPoint("cuTensorMapEncodeTiled", &fn, cudaEnableDefault, &qr) == cudaSuccess &&
            qr == cudaDriverEntryPointSuccess)
            encode = (EncodeFn)fn;
        (void)cudaGetLastError();
    }
    CUtensorMap tmk, tmv;
    memset(&tmk, 0, sizeof(tmk)); memset(&tmv, 0, sizeof(tmv));
    int use_tmap = 0;
    if (encode) {
        const cuuint64_t n_phys = (cuuint64_t)in_sizes[1] / (BS * HKV * DH);
        const cuuint64_t dims[4] = {64, (cuuint64_t)BS, (cuuint64_t)(HKV * 2), n_phys};
        const cuuint64_t strides[3] = {(cuuint64_t)TOK_BYTES, 128, (cuuint64_t)BS * TOK_BYTES};
        const cuuint32_t box[4] = {64, (cuuint32_t)CH_TOK, (cuuint32_t)(HKV * 2), 1};
        const cuuint32_t es[4] = {1, 1, 1, 1};
        const CUresult r1 = encode(&tmk, CU_TENSOR_MAP_DATA_TYPE_BFLOAT16, 4, (void*)kc, dims, strides, box, es,
                                   CU_TENSOR_MAP_INTERLEAVE_NONE, CU_TENSOR_MAP_SWIZZLE_128B,
                                   CU_TENSOR_MAP_L2_PROMOTION_NONE, CU_TENSOR_MAP_FLOAT_OOB_FILL_NONE);
        const CUresult r2 = encode(&tmv, CU_TENSOR_MAP_DATA_TYPE_BFLOAT16, 4, (void*)vc, dims, strides, box, es,
                                   CU_TENSOR_MAP_INTERLEAVE_NONE, CU_TENSOR_MAP_SWIZZLE_128B,
                                   CU_TENSOR_MAP_L2_PROMOTION_NONE, CU_TENSOR_MAP_FLOAT_OOB_FILL_NONE);
        use_tmap = (r1 == CUDA_SUCCESS && r2 == CUDA_SUCCESS) ? 1 : 0;
    }
    for (int b = 0; b < B; b++) {
        const __nv_bfloat16* qb = q + (size_t)b * H * DH;
        __nv_bfloat16* ob = out + (size_t)b * H * DH;
        if (use_tmap)
            decode_kernel<true><<<grid, NTHREADS, MAX_SMEM, cudaStreamPerThread>>>(qb, kc, vc, bt + (size_t)b * nb, ctx + b, ob, nb, 2, tmk, tmv);
        else
            decode_kernel<false><<<grid, NTHREADS, MAX_SMEM, cudaStreamPerThread>>>(qb, kc, vc, bt + (size_t)b * nb, ctx + b, ob, nb, 2, tmk, tmv);
    }
}
```

```cpp
#include <cuda_runtime.h>
#include <cuda.h>
#include <cuda_bf16.h>
#include <stdint.h>
#include <string.h>

namespace {

constexpr int H = 32, HKV = 16, DH = 128, BS = 16;
constexpr int TOK_BYTES = HKV * DH * 2;
constexpr int CH_TOK = 4;
constexpr int CH_BYTES = CH_TOK * TOK_BYTES;
constexpr int NCH = 7;
constexpr int GATE_K = 96;
constexpr int NSLOT = 2 * NCH;
constexpr int NCONS = 4;
constexpr int NHELP = 8;
constexpr int NWARPS = NCONS + 1 + NHELP;
constexpr int NTHREADS = NWARPS * 32;
constexpr int MAXG = 160;
constexpr int NGRP = NHELP * 4;
constexpr int NPASS = MAXG / NGRP;
constexpr int SMEM_RING = NSLOT * CH_BYTES;
constexpr int MIN_SMEM = 120 * 1024;
constexpr int MAX_SMEM = (SMEM_RING > MIN_SMEM) ? SMEM_RING : MIN_SMEM;
static_assert(NSLOT - 2 <= NWARPS, "prologue issue uses one warp per slot");

constexpr float NEG_INIT = -1.0e30f;
constexpr float LOG2E = 1.4426950408889634f;
constexpr float QK_SCALE = 0.08838834764831845f * LOG2E;
constexpr float MASKED = -998244352.0f * LOG2E;

__device__ uint2 g_rec[H * 4 * MAXG * 8];
__device__ uint2 g_ml[MAXG * H];
__device__ unsigned int g_epoch;
__device__ unsigned int g_cnt[2][3 * 32];

__device__ __forceinline__ uint32_t smem_u32(const void* p) { return (uint32_t)__cvta_generic_to_shared(p); }
__device__ __forceinline__ void mbar_init(uint32_t bar, int cnt) {
    asm volatile("mbarrier.init.shared::cta.b64 [%0], %1;" ::"r"(bar), "r"(cnt) : "memory");
}
__device__ __forceinline__ void mbar_expect_tx(uint32_t bar, uint32_t bytes) {
    asm volatile("mbarrier.arrive.expect_tx.shared::cta.b64 _, [%0], %1;" ::"r"(bar), "r"(bytes) : "memory");
}
__device__ __forceinline__ void mbar_arrive(uint32_t bar) {
    asm volatile("mbarrier.arrive.shared::cta.b64 _, [%0];" ::"r"(bar) : "memory");
}
__device__ __forceinline__ bool mbar_try(uint32_t bar, uint32_t parity) {
    uint32_t ok;
    asm volatile(
        "{\n.reg .pred p;\n"
        "mbarrier.try_wait.parity.shared::cta.b64 p, [%1], %2;\n"
        "selp.u32 %0, 1, 0, p;\n}"
        : "=r"(ok) : "r"(bar), "r"(parity) : "memory");
    return ok != 0;
}
__device__ __forceinline__ void mbar_wait(uint32_t bar, uint32_t parity) {
    if (mbar_try(bar, parity)) return;
    uint32_t n = 0;
    while (!mbar_try(bar, parity)) {
        if (++n > (1u << 24)) __trap();
    }
}
__device__ __forceinline__ void bulk_g2s_ef(uint32_t dst, const void* src, uint32_t bytes, uint32_t bar, uint64_t pol) {
    asm volatile("cp.async.bulk.shared::cluster.global.mbarrier::complete_tx::bytes.L2::cache_hint [%0], [%1], %2, [%3], %4;"
                 ::"r"(dst), "l"(src), "r"(bytes), "r"(bar), "l"(pol) : "memory");
}
template <bool TMAP>
__device__ __forceinline__ void load_chunk(uint32_t dst, const CUtensorMap* tm, const uint8_t* base,
                                           int page, int ch, uint32_t bar, uint64_t pol) {
    if (TMAP) {
        asm volatile("cp.async.bulk.tensor.4d.shared::cluster.global.mbarrier::complete_tx::bytes.L2::cache_hint "
                     "[%0], [%1, {%3, %4, %5, %6}], [%2], %7;"
                     ::"r"(dst), "l"(tm), "r"(bar), "r"(0), "r"((ch & 3) * CH_TOK), "r"(0), "r"(page), "l"(pol) : "memory");
    } else {
        const size_t off = ((size_t)page * BS + (size_t)((ch & 3) * CH_TOK)) * TOK_BYTES;
        bulk_g2s_ef(dst, base + off, CH_BYTES, bar, pol);
    }
}
__device__ __forceinline__ uint64_t policy_evict_first() {
    uint64_t pol;
    asm volatile("createpolicy.fractional.L2::evict_first.b64 %0, 1.0;" : "=l"(pol));
    return pol;
}
__device__ __forceinline__ void ldsm4(uint32_t (&r)[4], uint32_t addr) {
    asm volatile("ldmatrix.sync.aligned.m8n8.x4.shared.b16 {%0,%1,%2,%3}, [%4];"
                 : "=r"(r[0]), "=r"(r[1]), "=r"(r[2]), "=r"(r[3]) : "r"(addr) : "memory");
}
__device__ __forceinline__ void ldsm4t(uint32_t (&r)[4], uint32_t addr) {
    asm volatile("ldmatrix.sync.aligned.m8n8.x4.trans.shared.b16 {%0,%1,%2,%3}, [%4];"
                 : "=r"(r[0]), "=r"(r[1]), "=r"(r[2]), "=r"(r[3]) : "r"(addr) : "memory");
}
__device__ __forceinline__ void mma16816(float (&c)[4], const uint32_t (&a)[4], uint32_t b0, uint32_t b1) {
    asm volatile("mma.sync.aligned.m16n8k16.row.col.f32.bf16.bf16.f32 {%0,%1,%2,%3}, {%4,%5,%6,%7}, {%8,%9}, {%0,%1,%2,%3};"
                 : "+f"(c[0]), "+f"(c[1]), "+f"(c[2]), "+f"(c[3])
                 : "r"(a[0]), "r"(a[1]), "r"(a[2]), "r"(a[3]), "r"(b0), "r"(b1));
}
__device__ __forceinline__ uint32_t movm(uint32_t a) {
    uint32_t d;
    asm volatile("movmatrix.sync.aligned.m8n8.trans.b16 %0, %1;" : "=r"(d) : "r"(a));
    return d;
}
__device__ __forceinline__ uint32_t pack_bf16(float lo, float hi) {
    uint32_t d;
    asm("cvt.rn.bf16x2.f32 %0, %1, %2;" : "=r"(d) : "f"(hi), "f"(lo));
    return d;
}
__device__ __forceinline__ float ex2(float x) {
    float y;
    asm("ex2.approx.ftz.f32 %0, %1;" : "=f"(y) : "f"(x));
    return y;
}
__device__ __forceinline__ int ld_nc_i32(const int* p) {
    int v;
    asm volatile("ld.global.nc.s32 %0, [%1];" : "=r"(v) : "l"(p));
    return v;
}
__device__ __forceinline__ uint32_t nz(float f) {
    const uint32_t u = __float_as_uint(f);
    return u == 0u ? 0x80000000u : u;
}
__device__ __forceinline__ void st4v(void* p, uint32_t a, uint32_t b, uint32_t c, uint32_t d) {
    asm volatile("st.relaxed.gpu.global.v4.u32 [%0], {%1,%2,%3,%4};" ::"l"(p), "r"(a), "r"(b), "r"(c), "r"(d) : "memory");
}
__device__ __forceinline__ uint32_t nzu(uint32_t u) { return u == 0u ? 0x80000000u : u; }
__device__ __forceinline__ void st4_pred(uint4* p, uint32_t a, uint32_t b, uint32_t c, uint32_t d, int pred) {
    asm volatile("{\n.reg .pred p;\nsetp.ne.s32 p, %5, 0;\n@p st.relaxed.gpu.global.v4.u32 [%0], {%1,%2,%3,%4};\n}"
                 ::"l"(p), "r"(a), "r"(b), "r"(c), "r"(d), "r"(pred) : "memory");
}
__device__ __forceinline__ void st2_pred(uint2* p, uint32_t a, uint32_t b, int pred) {
    asm volatile("{\n.reg .pred p;\nsetp.ne.s32 p, %3, 0;\n@p st.relaxed.gpu.global.v2.u32 [%0], {%1,%2};\n}"
                 ::"l"(p), "r"(a), "r"(b), "r"(pred) : "memory");
}
__device__ __forceinline__ void ld2_pred(uint2& v, const uint2* p, int pred) {
    asm volatile("{\n.reg .pred p;\nsetp.ne.s32 p, %3, 0;\n@p ld.relaxed.gpu.global.v2.u32 {%0,%1}, [%2];\n}"
                 : "+r"(v.x), "+r"(v.y) : "l"(p), "r"(pred) : "memory");
}
__device__ __forceinline__ void named_bar(int id, int n) {
    asm volatile("bar.sync %0, %1;" ::"r"(id), "r"(n) : "memory");
}

template <bool TMAP>
__global__ void __launch_bounds__(NTHREADS, 1)
decode_kernel(const __nv_bfloat16* __restrict__ q, const uint8_t* __restrict__ kc, const uint8_t* __restrict__ vc,
              const int* __restrict__ bt, const int* __restrict__ ctx_ptr, __nv_bfloat16* __restrict__ out,
              int nb, int npass,
              const __grid_constant__ CUtensorMap tmk, const __grid_constant__ CUtensorMap tmv)
{
    extern __shared__ __align__(1024) uint8_t smem[];
    __shared__ __align__(8) uint64_t s_full[NSLOT], s_empty[NSLOT], s_done, s_clr;
    __shared__ int s_chunk[NCH];
    __shared__ unsigned int s_epoch;
    __shared__ __align__(16) float s_red[NHELP][32];
    __shared__ float2 s_ml[NHELP];

    const int tid = threadIdx.x, lane = tid & 31;
    const int warp = __shfl_sync(0xffffffffu, tid >> 5, 0);
    const int G = gridDim.x, cta = blockIdx.x;
    const int Lk = nb * BS;
    const uint32_t smem_base = smem_u32(smem);
    int ctx = ld_nc_i32(ctx_ptr);
    const int ch0 = (warp >> 1) * G + cta;
    const bool fill = warp < NSLOT - 2;
    int page0 = 0;
    if (lane == 0 && fill && (ch0 >> 2) < nb) page0 = ld_nc_i32(bt + (ch0 >> 2));
    if (lane == 0) {
        if (warp < NSLOT) {
            const int s = warp;
            const int ch = ch0;
            const int page = page0;
            if (TMAP) asm volatile("prefetch.tensormap [%0];" ::"l"((s & 1) ? &tmv : &tmk) : "memory");
            const uint32_t fb = smem_u32(&s_full[s]);
            mbar_init(fb, 1);
            mbar_init(smem_u32(&s_empty[s]), NCONS);
            asm volatile("fence.mbarrier_init.release.cluster;" ::: "memory");
            const int cx = min(max(ctx, 0), Lk);
            if (fill) {
                if (ch * CH_TOK < cx) {
                    mbar_expect_tx(fb, CH_BYTES);
                    load_chunk<TMAP>(smem_base + s * CH_BYTES, (s & 1) ? &tmv : &tmk, (s & 1) ? vc : kc, page, ch, fb, policy_evict_first());
                    if (!(s & 1)) s_chunk[s >> 1] = ch;
                } else if (!(s & 1)) {
                    s_chunk[s >> 1] = -1;
                    mbar_arrive(fb);
                }
            }
        }
        if (warp == NWARPS - 1) {
            mbar_init(smem_u32(&s_done), NCONS);
            mbar_init(smem_u32(&s_clr), NHELP);
#pragma unroll
            for (int s = NWARPS; s < NSLOT; s++) { mbar_init(smem_u32(&s_full[s]), 1); mbar_init(smem_u32(&s_empty[s]), NCONS); }
            asm volatile("fence.mbarrier_init.release.cluster;" ::: "memory");
        }
    }
    unsigned int nxt = 0;
    unsigned int* cnt = nullptr;
    if (tid == NCONS * 32) {
        unsigned int epoch;
        asm volatile("ld.relaxed.gpu.global.u32 %0, [%1];" : "=r"(epoch) : "l"(&g_epoch) : "memory");
        s_epoch = epoch;
        cnt = g_cnt[epoch & 1];
        nxt = atomicAdd(cnt, 1u);
        if (cta == 0) { unsigned int* o = g_cnt[(epoch & 1) ^ 1]; o[0] = 0; o[32] = 0; o[64] = 0; }
    }
    ctx = min(max(ctx, 0), Lk);
    const int nchunks = (ctx + CH_TOK - 1) / CH_TOK;
    __syncwarp();
    asm volatile("bar.arrive %0, %1;" ::"r"(warp < NCONS ? 0 : 3), "r"(NTHREADS) : "memory");

    if (warp == NCONS) {
        named_bar(0, NTHREADS);
        if (lane == 0) {
            {
                int j = NCH - 1;
                uint32_t ph = 1;
                const uint64_t pol = policy_evict_first();
                int ch = (NCH - 1) * G + cta;
                while (true) {
                    const uint32_t fK = smem_u32(&s_full[2 * j]), fV = fK + 8;
                    const uint32_t eK = smem_u32(&s_empty[2 * j]), eV = eK + 8;
                    if (ch >= nchunks) {
                        mbar_wait(eK, ph);
                        s_chunk[j] = -1;
                        mbar_arrive(fK);
                        break;
                    }
                    int page = ld_nc_i32(bt + (ch >> 2));
                    page = __shfl_sync(1u, page, 0);
                    const uint32_t dst = smem_base + (2 * j) * CH_BYTES;
                    mbar_wait(eK, ph);
                    s_chunk[j] = ch;
                    mbar_expect_tx(fK, CH_BYTES);
                    load_chunk<TMAP>(dst, &tmk, kc, page, ch, fK, pol);
                    mbar_wait(eV, ph);
                    mbar_expect_tx(fV, CH_BYTES);
                    load_chunk<TMAP>(dst + CH_BYTES, &tmv, vc, page, ch, fV, pol);
                    if (++j == NCH) { j = 0; ph ^= 1; }
                    ch = NCH * G + (int)nxt;
                    if (ch < nchunks) nxt = atomicAdd(cnt, 1u);
                }
            }
            mbar_wait(smem_u32(&s_done), 0);
            asm volatile("red.relaxed.gpu.global.add.u32 [%0], 1;" ::"l"(cnt + 32) : "memory");
        }
    } else if (warp < NCONS) {
        const int w = warp;
        uint32_t qf[8][2];
        {
            const int n = lane >> 2, h = lane >> 3;
            const uint32_t* qrow = reinterpret_cast<const uint32_t*>(q + (size_t)(8 * w + n) * DH);
#pragma unroll
            for (int j = 0; j < 8; j++) {
                const int d0 = 16 * (j ^ h) + (lane & 3) * 2;
                qf[j][0] = __ldg(qrow + (d0 >> 1));
                qf[j][1] = __ldg(qrow + ((d0 + 8) >> 1));
            }
        }
        uint32_t koff[2], voff[2];
        {
            const int mi = lane >> 3, r = lane & 7, h = r & 3;
            const int tK = (r >> 2) + 2 * (mi & 1), bK = mi >> 1;
            const int tV = (r >> 2) + 2 * (mi >> 1), bV = mi & 1;
            if (TMAP) {
                koff[0] = ((8 * w + 2 * h) * 4 + tK) * 128 + (((2 * h + bK) ^ tK) << 4);
                voff[0] = ((8 * w + 2 * h) * 4 + tV) * 128 + (((2 * h + bV) ^ tV) << 4);
                koff[1] = (koff[0] + 512) ^ 64;
                voff[1] = (voff[0] + 512) ^ 64;
            } else {
                koff[0] = tK * TOK_BYTES + (4 * w + h) * 256 + ((2 * h + bK) << 4);
                voff[0] = tV * TOK_BYTES + (4 * w + h) * 256 + ((2 * h + bV) << 4);
                koff[1] = koff[0] ^ 128;
                voff[1] = voff[0] ^ 128;
            }
            voff[0] += CH_BYTES; voff[1] += CH_BYTES;
        }
        const bool valid_lane = (((lane >> 2) & 3) == (lane & 3));
        const int tokA = lane >> 4;
        const int src0 = 5 * (lane & 3), src1 = src0 + 16;

        float acc[8][4];
#pragma unroll
        for (int i = 0; i < 8; i++) { acc[i][0] = acc[i][1] = acc[i][2] = acc[i][3] = 0.f; }
        float m0 = NEG_INIT, m1 = NEG_INIT, l0 = 0.f, l1 = 0.f;

#pragma unroll 1
        for (int pass = 0; pass < npass; pass++) {
            {
                int j = 0;
                uint32_t ph = 0;
                while (true) {
                    const uint32_t fK = smem_u32(&s_full[2 * j]), eK = smem_u32(&s_empty[2 * j]);
                    int chunk = 0;
                    if (pass) {
                        mbar_wait(fK, ph);
                        chunk = *(volatile int*)&s_chunk[j];
                    }
                    if (chunk < 0) break;
                    const uint32_t sb = smem_base + (2 * j) * CH_BYTES;
                    float c0[4] = {0.f, 0.f, 0.f, 0.f}, c1[4] = {0.f, 0.f, 0.f, 0.f};
                    {
                        uint32_t a[8][4];
#pragma unroll
                        for (int jj = 0; jj < 8; jj++) ldsm4(a[jj], (sb + koff[jj >> 2]) ^ ((jj & 3) << 5));
                        __syncwarp();
                        if (pass && lane == 0) mbar_arrive(eK);
#pragma unroll
                        for (int jj = 0; jj < 8; jj += 2) {
                            mma16816(c0, a[jj], qf[jj][0], qf[jj][1]);
                            mma16816(c1, a[jj + 1], qf[jj + 1][0], qf[jj + 1][1]);
                        }
                    }
                    uint32_t av[8][4];
                    if (pass) mbar_wait(fK + 8, ph);
                    {
#pragma unroll
                        for (int i = 0; i < 8; i++) ldsm4t(av[i], (sb + voff[i >> 2]) ^ ((i & 3) << 5));
                        __syncwarp();
                        if (pass && lane == 0) mbar_arrive(eK + 8);
                    }
                    const int rem = ctx - chunk * CH_TOK;
                    const bool vA = valid_lane && (tokA < rem), vB = valid_lane && (tokA + 2 < rem);
                    const float NINF = __int_as_float(0xff800000);
                    const float s0 = vA ? (c0[0] + c1[0]) * QK_SCALE : NINF;
                    const float s1 = vA ? (c0[1] + c1[1]) * QK_SCALE : NINF;
                    const float s2 = vB ? (c0[2] + c1[2]) * QK_SCALE : NINF;
                    const float s3 = vB ? (c0[3] + c1[3]) * QK_SCALE : NINF;
                    const float x0 = fmaxf(s0, s2), x1 = fmaxf(s1, s3);
                    const float y0 = fmaxf(__shfl_sync(0xffffffffu, x0, src0), __shfl_sync(0xffffffffu, x0, src1));
                    const float y1 = fmaxf(__shfl_sync(0xffffffffu, x1, src0), __shfl_sync(0xffffffffu, x1, src1));
                    const float n0 = fmaxf(m0, y0), n1 = fmaxf(m1, y1);
                    if (__any_sync(0xffffffffu, (n0 > m0) || (n1 > m1))) {
                        const float a0 = ex2(m0 - n0), a1 = ex2(m1 - n1);
                        l0 *= a0; l1 *= a1;
#pragma unroll
                        for (int i = 0; i < 8; i++) {
                            acc[i][0] *= a0; acc[i][1] *= a1; acc[i][2] *= a0; acc[i][3] *= a1;
                        }
                        m0 = n0; m1 = n1;
                    }
                    const float p0 = ex2(s0 - m0), p1 = ex2(s1 - m1), p2 = ex2(s2 - m0), p3 = ex2(s3 - m1);
                    l0 += p0 + p2; l1 += p1 + p3;
                    const uint32_t pb0 = movm(pack_bf16(p0, p1));
                    const uint32_t pb1 = movm(pack_bf16(p2, p3));
#pragma unroll
                    for (int i = 0; i < 8; i++) mma16816(acc[i], av[i], pb0, pb1);
                    if (!pass) break;
                    if (++j == NCH) { j = 0; ph ^= 1; }
                }
            }
            const int h = lane & 3, g = lane >> 2;
            const int rec0 = ((8 * w + 2 * h) * 4) * MAXG + cta;
            if (pass) mbar_wait(smem_u32(&s_clr), 0);
            const float r0 = __shfl_sync(0xffffffffu, l0, src0) + __shfl_sync(0xffffffffu, l0, src1);
            const float r1 = __shfl_sync(0xffffffffu, l1, src0) + __shfl_sync(0xffffffffu, l1, src1);
            st4_pred(reinterpret_cast<uint4*>(g_ml + cta * H + 8 * w + 2 * h), nz(m0), nz(r0), nz(m1), nz(r1), pass && lane < 4);
#pragma unroll
            for (int i0 = 0; i0 < 8; i0 += 2) {
                const int qd = (i0 >> 1) ^ (h >> 1);
                uint2* p = g_rec + (size_t)(rec0 + qd * MAXG) * 8 + g;
                st2_pred(p, nzu(pack_bf16(acc[i0][0], acc[i0][2])), nzu(pack_bf16(acc[i0 + 1][0], acc[i0 + 1][2])), pass);
                st2_pred(p + (size_t)4 * MAXG * 8, nzu(pack_bf16(acc[i0][1], acc[i0][3])), nzu(pack_bf16(acc[i0 + 1][1], acc[i0 + 1][3])), pass);
            }
            __syncwarp();
            if (pass && lane == 0) mbar_arrive(smem_u32(&s_done));
            if (!pass) {
#pragma unroll
                for (int i = 0; i < 8; i++) { acc[i][0] = acc[i][1] = acc[i][2] = acc[i][3] = 0.f; }
                m0 = NEG_INIT; m1 = NEG_INIT; l0 = 0.f; l1 = 0.f;
                named_bar(3, NTHREADS);
            }
        }
    } else {
        const int hw = warp - NCONS - 1;
        const int t = tid - (NCONS + 1) * 32;
        const int grp = t >> 3, x = t & 7;
        named_bar(0, NTHREADS);
        const unsigned int epoch = s_epoch;
        unsigned int* cnt = g_cnt[epoch & 1];
        for (int i = t; i < H * 4 * 4; i += NHELP * 32)
            st4v(g_rec + ((size_t)(i >> 2) * MAXG + cta) * 8 + (i & 3) * 2, 0u, 0u, 0u, 0u);
        if (t < 16) st4v(g_ml + cta * H + 2 * t, 0u, 0u, 0u, 0u);
        __syncwarp();
        if (lane == 0) {
            asm volatile("red.release.gpu.global.add.u32 [%0], 1;" ::"l"(cnt + 64) : "memory");
            asm volatile("fence.acq_rel.gpu;" ::: "memory");
            mbar_arrive(smem_u32(&s_clr));
        }
#pragma unroll 1
        for (int pass = 0; pass < npass; pass++) {
            if (pass && t == 0 && cta < H * 4) {
                uint32_t n = 0;
                while (true) {
                    unsigned int u;
                    asm volatile("ld.acquire.gpu.global.u32 %0, [%1];" : "=r"(u) : "l"(cnt + 64) : "memory");
                    if (u >= (unsigned)(NHELP * G)) break;
                    if (++n > (1u << 24)) __trap();
                    __nanosleep(500);
                }
                if (cta == 0) g_epoch = epoch + 1;
                const unsigned int target = (G > GATE_K) ? (unsigned)(G - GATE_K) : 0u;
                n = 0;
                while (true) {
                    unsigned int v;
                    asm volatile("ld.relaxed.gpu.global.u32 %0, [%1];" : "=r"(v) : "l"(cnt + 32) : "memory");
                    if (v >= target) break;
                    if (++n > (1u << 24)) __trap();
                    __nanosleep(v == 0 ? 400 : 0);
                }
            }
            named_bar(1, NHELP * 32);
#pragma unroll 1
            for (int mr = cta; mr < H * 4; mr += G) {

                const uint2* rp = g_rec + (size_t)mr * MAXG * 8 + x;
                uint2 v[NPASS];
                const uint2* mp = g_ml + (mr >> 2);
                uint2 ml[NPASS];
                uint32_t pend = 0;
#pragma unroll
                for (int p = 0; p < NPASS; p++) {
                    v[p] = make_uint2(0x80000000u, 0x80000000u);
                    ml[p] = make_uint2(__float_as_uint(NEG_INIT), 0x80000000u);
                    if (pass && grp + p * NGRP < G) pend |= 1u << p;
                }
                uint32_t n = 0;
                do {
#pragma unroll
                    for (int p = 0; p < NPASS; p++) {
                        const int c = grp + p * NGRP;
                        ld2_pred(v[p], rp + c * 8, pend & (1u << p));
                        ld2_pred(ml[p], mp + c * H, pend & (1u << p));
                    }
#pragma unroll
                    for (int p = 0; p < NPASS; p++) {
                        const bool ok = v[p].x && v[p].y && ml[p].x && ml[p].y;
                        if (ok) pend &= ~(1u << p);
                    }
                    if (++n > (1u << 22)) __trap();
                } while (pend);
                __syncwarp();
                float Mw = NEG_INIT;
#pragma unroll
                for (int p = 0; p < NPASS; p++) Mw = fmaxf(Mw, __uint_as_float(ml[p].x));
                Mw = fmaxf(Mw, __shfl_xor_sync(0xffffffffu, Mw, 8));
                Mw = fmaxf(Mw, __shfl_xor_sync(0xffffffffu, Mw, 16));
                float a0 = 0.f, a1 = 0.f, a2 = 0.f, a3 = 0.f, al = 0.f;
#pragma unroll
                for (int p = 0; p < NPASS; p++) {
                    const float wgt = ex2(__uint_as_float(ml[p].x) - Mw);
                    a0 += wgt * __uint_as_float(v[p].x << 16); a1 += wgt * __uint_as_float(v[p].x & 0xffff0000u);
                    a2 += wgt * __uint_as_float(v[p].y << 16); a3 += wgt * __uint_as_float(v[p].y & 0xffff0000u);
                    al += wgt * __uint_as_float(ml[p].y);
                }
#pragma unroll
                for (int o = 8; o < 32; o <<= 1) {
                    a0 += __shfl_xor_sync(0xffffffffu, a0, o);
                    a1 += __shfl_xor_sync(0xffffffffu, a1, o);
                    a2 += __shfl_xor_sync(0xffffffffu, a2, o);
                    a3 += __shfl_xor_sync(0xffffffffu, a3, o);
                    al += __shfl_xor_sync(0xffffffffu, al, o);
                }
                if (lane < 8) *reinterpret_cast<float4*>(&s_red[hw][lane * 4]) = make_float4(a0, a1, a2, a3);
                if (lane == 0) s_ml[hw] = make_float2(Mw, al);
                named_bar(1, NHELP * 32);
                if (hw == 0) {
                    float M = NEG_INIT;
                    float2 wml[NHELP];
#pragma unroll
                    for (int k = 0; k < NHELP; k++) { wml[k] = s_ml[k]; M = fmaxf(M, wml[k].x); }
                    float r = 0.f, L = 0.f;
#pragma unroll
                    for (int k = 0; k < NHELP; k++) {
                        const float wgt = ex2(wml[k].x - M);
                        r += wgt * s_red[k][lane];
                        L += wgt * wml[k].y;
                    }
                    const int head = mr >> 2, qd = mr & 3, h = (head >> 1) & 3;
                    const int d = qd * 32 + 16 * (((lane >> 1) & 1) ^ (h & 1)) + 8 * (lane & 1) + (lane >> 2);
                    if (pass && M < MASKED + 150.f) {
                        const float Mall = fmaxf(M, MASKED);
                        const float wa = ex2(M - Mall), wb = ex2(MASKED - Mall);
                        float sv = 0.f;
                        for (int tk = ctx; tk < Lk; tk++) {
                            const int pg = bt[tk >> 4];
                            const __nv_bfloat16* vp = reinterpret_cast<const __nv_bfloat16*>(
                                vc + ((size_t)pg * BS + (tk & 15)) * TOK_BYTES) + (head >> 1) * DH + d;
                            sv += __bfloat162float(*vp);
                        }
                        r = wa * r + wb * sv;
                        L = wa * L + wb * (float)(Lk - ctx);
                    }
                    const __nv_bfloat16 o = __float2bfloat16(__fdividef(r, L));
                    if (pass) out[head * DH + d] = o;
                }
                if (!pass || mr + G >= H * 4) break;
                named_bar(1, NHELP * 32);
            }
        }
    }
}

}

extern "C" void kernel_launch(void* const* d_in, const int* in_sizes, int n_in, void* d_out, int out_size) {
    (void)n_in; (void)out_size;
    const __nv_bfloat16* q = (const __nv_bfloat16*)d_in[0];
    const uint8_t* kc = (const uint8_t*)d_in[1];
    const uint8_t* vc = (const uint8_t*)d_in[2];
    const int* bt = (const int*)d_in[3];
    const int* ctx = (const int*)d_in[4];
    __nv_bfloat16* out = (__nv_bfloat16*)d_out;
    const int B = in_sizes[4];
    const int nb = in_sizes[3] / B;

    typedef CUresult (*EncodeFn)(CUtensorMap*, CUtensorMapDataType, cuuint32_t, void*, const cuuint64_t*, const cuuint64_t*,
                                 const cuuint32_t*, const cuuint32_t*, CUtensorMapInterleave, CUtensorMapSwizzle,
                                 CUtensorMapL2promotion, CUtensorMapFloatOOBfill);
    static int grid = 0;
    static EncodeFn encode = nullptr;
    if (grid == 0) {
        int dev = 0, sms = 0;
        cudaGetDevice(&dev);
        cudaDeviceGetAttribute(&sms, cudaDevAttrMultiProcessorCount, dev);
        cudaFuncSetAttribute(decode_kernel<true>, cudaFuncAttributeMaxDynamicSharedMemorySize, MAX_SMEM);
        cudaFuncSetAttribute(decode_kernel<false>, cudaFuncAttributeMaxDynamicSharedMemorySize, MAX_SMEM);
        grid = sms < MAXG ? sms : MAXG;
        void* fn = nullptr;
        cudaDriverEntryPointQueryResult qr;
        if (cudaGetDriverEntryPoint("cuTensorMapEncodeTiled", &fn, cudaEnableDefault, &qr) == cudaSuccess &&
            qr == cudaDriverEntryPointSuccess)
            encode = (EncodeFn)fn;
        (void)cudaGetLastError();
    }
    CUtensorMap tmk, tmv;
    memset(&tmk, 0, sizeof(tmk)); memset(&tmv, 0, sizeof(tmv));
    int use_tmap = 0;
    if (encode) {
        const cuuint64_t n_phys = (cuuint64_t)in_sizes[1] / (BS * HKV * DH);
        const cuuint64_t dims[4] = {64, (cuuint64_t)BS, (cuuint64_t)(HKV * 2), n_phys};
        const cuuint64_t strides[3] = {(cuuint64_t)TOK_BYTES, 128, (cuuint64_t)BS * TOK_BYTES};
        const cuuint32_t box[4] = {64, (cuuint32_t)CH_TOK, (cuuint32_t)(HKV * 2), 1};
        const cuuint32_t es[4] = {1, 1, 1, 1};
        const CUresult r1 = encode(&tmk, CU_TENSOR_MAP_DATA_TYPE_BFLOAT16, 4, (void*)kc, dims, strides, box, es,
                                   CU_TENSOR_MAP_INTERLEAVE_NONE, CU_TENSOR_MAP_SWIZZLE_128B,
                                   CU_TENSOR_MAP_L2_PROMOTION_NONE, CU_TENSOR_MAP_FLOAT_OOB_FILL_NONE);
        const CUresult r2 = encode(&tmv, CU_TENSOR_MAP_DATA_TYPE_BFLOAT16, 4, (void*)vc, dims, strides, box, es,
                                   CU_TENSOR_MAP_INTERLEAVE_NONE, CU_TENSOR_MAP_SWIZZLE_128B,
                                   CU_TENSOR_MAP_L2_PROMOTION_NONE, CU_TENSOR_MAP_FLOAT_OOB_FILL_NONE);
        use_tmap = (r1 == CUDA_SUCCESS && r2 == CUDA_SUCCESS) ? 1 : 0;
    }
    for (int b = 0; b < B; b++) {
        const __nv_bfloat16* qb = q + (size_t)b * H * DH;
        __nv_bfloat16* ob = out + (size_t)b * H * DH;
        if (use_tmap)
            decode_kernel<true><<<grid, NTHREADS, MAX_SMEM, cudaStreamPerThread>>>(qb, kc, vc, bt + (size_t)b * nb, ctx + b, ob, nb, 2, tmk, tmv);
        else
            decode_kernel<false><<<grid, NTHREADS, MAX_SMEM, cudaStreamPerThread>>>(qb, kc, vc, bt + (size_t)b * nb, ctx + b, ob, nb, 2, tmk, tmv);
    }
}
```
